```python
import torch

def _softmax(x, axis=-1):
    return torch.softmax(x, dim=axis)

def _gelu(x):
    return torch.nn.functional.gelu(x, approximate='tanh')

def _silu(x):
    return torch.nn.functional.silu(x)

def _sigmoid(x):
    return torch.sigmoid(x)

def _layernorm(x, axis=-1, eps=1e-05):
    m = x.mean(dim=axis, keepdim=True)
    v = x.var(dim=axis, keepdim=True, unbiased=False)
    return (x - m) / torch.sqrt(v + eps)

def _scatter_add(tgt, idx, src, axis=0):
    return tgt.clone().index_add_(axis, idx, src)

def _segment_sum(src, seg, n):
    out = torch.zeros((n,) + src.shape[1:], dtype=src.dtype)
    return out.index_add_(0, seg, src)

def _pad(x, pw):
    flat = tuple((v for pair in reversed(pw) for v in pair))
    return torch.nn.functional.pad(x, flat)
kernel_name = 'concat_heads__memory_aug_recurrent_mem_tr__ssm_conv_h3__prompt'

def setup_inputs():

    _w = lambda a: (lambda t: t.to(torch.bfloat16) if t.is_floating_point() else t)(torch.as_tensor(a))

    def _A_setup():
        B, S, Dm = (1, 2048, 640)
        H, Dh = (32, 128)
        M, seg = (8, 32)
        seg = min(seg, S)
        S = S // seg * seg
        return {'x': _w((lambda *s: torch.randn(*s, dtype=torch.bfloat16) * 0.05)(B, S, Dm)), 'mem0': _w((lambda *s: torch.randn(*s, dtype=torch.bfloat16) * 0.4)(B, M, Dm)), 'Wq': _w((lambda *s: torch.randn(*s, dtype=torch.bfloat16) * 6.4)(Dm, H, Dh) * Dm ** (-0.5)), 'Wk': _w((lambda *s: torch.randn(*s, dtype=torch.bfloat16) * 6.4)(Dm, H, Dh) * Dm ** (-0.5)), 'Wv': _w((lambda *s: torch.randn(*s, dtype=torch.bfloat16) * 0.4)(Dm, H, Dh) * Dm ** (-0.5)), 'Wo': _w((lambda *s: torch.randn(*s, dtype=torch.bfloat16) * 0.4)(H, Dh, Dm) * (H * Dh) ** (-0.5)), 'seg_len': seg}
    _A_in = _A_setup()

    def _B_setup():
        B, S, D = (1, 2048, 640)
        ks = 4
        return {'q': _w((lambda *s: torch.randn(*s, dtype=torch.bfloat16) * 0.05)(B, S, D)), 'k': _w((lambda *s: torch.randn(*s, dtype=torch.bfloat16) * 0.4)(B, S, D)), 'v': _w((lambda *s: torch.randn(*s, dtype=torch.bfloat16) * 0.4)(B, S, D)), 'shift_k': _w((lambda *s: torch.randn(*s, dtype=torch.bfloat16) * 0.4)(D, ks) * 0.5), 'ssm_k': _w((lambda *s: torch.randn(*s, dtype=torch.bfloat16) * 0.4)(D, S) * (1.0 / S ** 0.5)), 'ssm_D': _w((lambda *s: torch.randn(*s, dtype=torch.bfloat16) * 0.4)(D))}
    _B_in = _B_setup()
    return {'A_x': _A_in['x'], 'A_mem0': _A_in['mem0'], 'A_Wq': _A_in['Wq'], 'A_Wk': _A_in['Wk'], 'A_Wv': _A_in['Wv'], 'A_Wo': _A_in['Wo'], 'A_seg_len': _A_in['seg_len'], 'B_q': _B_in['q'], 'B_k': _B_in['k'], 'B_v': _B_in['v'], 'B_shift_k': _B_in['shift_k'], 'B_ssm_k': _B_in['ssm_k'], 'B_ssm_D': _B_in['ssm_D']}

def reference(A_x, A_mem0, A_Wq, A_Wk, A_Wv, A_Wo, A_seg_len, B_q, B_k, B_v, B_shift_k, B_ssm_k, B_ssm_D):

    def _A_ref(x, mem0, Wq, Wk, Wv, Wo, seg_len):
        B, S, Dm = x.shape
        H, Dh = (Wq.shape[1], Wq.shape[2])
        M = mem0.shape[1]
        scale = Dh ** (-0.5)
        n_seg = S // seg_len
        L = M + seg_len
        idx = torch.arange(L)
        mask = (idx[:, None] < M) | (idx[:, None] >= idx[None, :])
        mem = mem0
        outs = []
        for s in range(n_seg):
            xs = x[:, s * seg_len:(s + 1) * seg_len, :].clone()
            h = torch.concatenate([mem, xs], axis=1)
            q = torch.einsum('btd,dhe->bhte', h, Wq)
            k = torch.einsum('btd,dhe->bhte', h, Wk)
            v = torch.einsum('btd,dhe->bhte', h, Wv)
            scores = torch.einsum('bhqe,bhke->bhqk', q, k) * scale
            scores = torch.where(mask[None, None], scores, -1000000000.0)
            p = _softmax(scores, axis=-1)
            o = torch.einsum('bhqk,bhke->bhqe', p, v)
            o = torch.einsum('bhte,hed->btd', o, Wo)
            mem = o[:, :M, :].clone()
            outs.append(o[:, M:, :])
        return torch.concatenate(outs, axis=1)

    def _B_ref(q, k, v, shift_k, ssm_k, ssm_D):
        B, S, D = q.shape
        ks = shift_k.shape[-1]
        k_pad = _pad(k, ((0, 0), (ks - 1, 0), (0, 0)))
        k_shift = torch.zeros_like(k)
        for t in range(ks):
            k_shift = k_shift + k_pad[:, t:t + S, :] * shift_k[:, ks - 1 - t][None, None, :]
        kv = k_shift * v
        L = 2 * S
        kv_pad = _pad(kv, ((0, 0), (0, S), (0, 0)))
        kf_pad = _pad(ssm_k, ((0, 0), (0, S)))
        kv_f = (lambda x, axes=(-2, -1): torch.fft.rfft2(x.float(), dim=axes))(kv_pad[:, None, :, :], axes=(1, 2))
        kf_f = (lambda x, axes=(-2, -1): torch.fft.rfft2(x.float(), dim=axes))(kf_pad[:, None, :], axes=(1, 2))
        kf_f = (lambda x, *d: x.permute(*d))(kf_f, 1, 2, 0)
        y_f = kv_f * kf_f[None, :, :, :]
        y = (lambda x, s, axes=(-2, -1): torch.fft.irfft2(x, s=s, dim=axes).to(torch.bfloat16))(y_f, (1, L), axes=(1, 2))[:, 0, :S, :]
        y = y + kv * ssm_D[None, None, :]
        return q * y
    a = _A_ref(A_x, A_mem0, A_Wq, A_Wk, A_Wv, A_Wo, A_seg_len)
    b = _B_ref(B_q, B_k, B_v, B_shift_k, B_ssm_k, B_ssm_D)
    return torch.concatenate([a, b], axis=-1)
```

```cpp
#include <cuda_runtime.h>
#include <cuda_bf16.h>
#include <cuda.h>
#include <stdint.h>
#include <stdio.h>

typedef __nv_bfloat16 bf16;

constexpr int S_ = 2048, D_ = 640, H_ = 32, DH_ = 128, HD_ = 4096, NSEG = 64, SEG = 32, M_ = 8;

__device__ __align__(1024) bf16 g_KV[(size_t)S_ * 8192];
__device__ __align__(1024) bf16 g_KVM[(size_t)NSEG * H_ * 2 * M_ * DH_];
__device__ __align__(1024) bf16 g_O[(size_t)S_ * HD_];
__device__ __align__(1024) float g_acc4[8 * 8 * 160 * 4];
__device__ __align__(1024) float g_acc2[8 * 8 * 160 * 2];
__device__ __align__(1024) float g_part[2 * 5 * 8 * 128 * 128];
struct Flags {
  unsigned kv[16];
  unsigned mem[64];
  unsigned o[16];
  unsigned part[16];
  unsigned ticket, done;
};
__device__ Flags g_flags;

__device__ __forceinline__ uint32_t smem_u32(const void* p) { return (uint32_t)__cvta_generic_to_shared(p); }
__device__ __forceinline__ uint32_t mapa(uint32_t a, uint32_t r) {
  uint32_t o; asm("mapa.shared::cluster.u32 %0,%1,%2;" : "=r"(o) : "r"(a), "r"(r)); return o;
}
__device__ __forceinline__ void mbar_init(uint32_t a, uint32_t c) { asm volatile("mbarrier.init.shared::cta.b64 [%0],%1;" ::"r"(a), "r"(c) : "memory"); }
__device__ __forceinline__ void mbar_expect(uint32_t a, uint32_t tx) { asm volatile("mbarrier.arrive.expect_tx.shared::cta.b64 _,[%0],%1;" ::"r"(a), "r"(tx) : "memory"); }
__device__ __forceinline__ bool mbar_try(uint32_t a, uint32_t ph) {
  uint32_t ok;
  asm volatile("{\n.reg .pred p;\nmbarrier.try_wait.parity.shared::cta.b64 p,[%1],%2;\nselp.u32 %0,1,0,p;\n}" : "=r"(ok) : "r"(a), "r"(ph) : "memory");
  return ok;
}
__device__ __forceinline__ bool mbar_test(uint32_t a, uint32_t ph) {
  uint32_t ok;
  asm volatile("{\n.reg .pred p;\nmbarrier.test_wait.parity.shared::cta.b64 p,[%1],%2;\nselp.u32 %0,1,0,p;\n}" : "=r"(ok) : "r"(a), "r"(ph) : "memory");
  return ok;
}
constexpr int SPIN_LIMIT = 1 << 22;
__device__ __forceinline__ void mbar_wait(uint32_t a, uint32_t ph) {
  if (mbar_try(a, ph)) return;
  int n = 0;
  while (!mbar_try(a, ph)) { if (++n > SPIN_LIMIT) __trap(); }
}
__device__ __forceinline__ void bar_sync(int id, int n) { asm volatile("bar.sync %0,%1;" ::"r"(id), "r"(n) : "memory"); }
__device__ __forceinline__ void bar_arrive(int id, int n) { asm volatile("bar.arrive %0,%1;" ::"r"(id), "r"(n) : "memory"); }
__device__ __forceinline__ void st_async_b32(uint32_t a, uint32_t x, uint32_t mb) {
  asm volatile("st.async.weak.shared::cluster.mbarrier::complete_tx::bytes.b32 [%0],%1,[%2];" ::"r"(a), "r"(x), "r"(mb) : "memory");
}
__device__ __forceinline__ void st_async_v2(uint32_t a, uint32_t x, uint32_t y, uint32_t mb) {
  asm volatile("st.async.weak.shared::cluster.mbarrier::complete_tx::bytes.v2.b32 [%0],{%1,%2},[%3];" ::"r"(a), "r"(x), "r"(y), "r"(mb) : "memory");
}
__device__ __forceinline__ void ldsm4(uint32_t (&r)[4], uint32_t a) {
  asm volatile("ldmatrix.sync.aligned.m8n8.x4.shared.b16 {%0,%1,%2,%3},[%4];" : "=r"(r[0]), "=r"(r[1]), "=r"(r[2]), "=r"(r[3]) : "r"(a) : "memory");
}
__device__ __forceinline__ void ldsm2(uint32_t& r0, uint32_t& r1, uint32_t a) {
  asm volatile("ldmatrix.sync.aligned.m8n8.x2.shared.b16 {%0,%1},[%2];" : "=r"(r0), "=r"(r1) : "r"(a) : "memory");
}
__device__ __forceinline__ void ldsm4t(uint32_t (&r)[4], uint32_t a) {
  asm volatile("ldmatrix.sync.aligned.m8n8.x4.trans.shared.b16 {%0,%1,%2,%3},[%4];" : "=r"(r[0]), "=r"(r[1]), "=r"(r[2]), "=r"(r[3]) : "r"(a) : "memory");
}
__device__ __forceinline__ void stsm2t(uint32_t a, uint32_t r0, uint32_t r1) {
  asm volatile("stmatrix.sync.aligned.m8n8.x2.trans.shared.b16 [%0],{%1,%2};" ::"r"(a), "r"(r0), "r"(r1) : "memory");
}
__device__ __forceinline__ uint32_t movm(uint32_t a) {
  uint32_t d; asm volatile("movmatrix.sync.aligned.m8n8.trans.b16 %0,%1;" : "=r"(d) : "r"(a)); return d;
}
__device__ __forceinline__ void mma16816(float (&d)[4], const uint32_t (&a)[4], uint32_t b0, uint32_t b1) {
  asm volatile("mma.sync.aligned.m16n8k16.row.col.f32.bf16.bf16.f32 {%0,%1,%2,%3},{%4,%5,%6,%7},{%8,%9},{%0,%1,%2,%3};"
               : "+f"(d[0]), "+f"(d[1]), "+f"(d[2]), "+f"(d[3]) : "r"(a[0]), "r"(a[1]), "r"(a[2]), "r"(a[3]), "r"(b0), "r"(b1));
}
__device__ __forceinline__ void mma16816_h(float (&d)[4], uint32_t a0, uint32_t a2, uint32_t b0, uint32_t b1) {
  asm volatile("mma.sync.aligned.m16n8k16.row.col.f32.bf16.bf16.f32 {%0,%1,%2,%3},{%4,%5,%6,%5},{%7,%8},{%0,%1,%2,%3};"
               : "+f"(d[0]), "+f"(d[1]), "+f"(d[2]), "+f"(d[3]) : "r"(a0), "r"(0u), "r"(a2), "r"(b0), "r"(b1));
}
__device__ __forceinline__ void mma1688_h(float (&d)[4], uint32_t a0, uint32_t b0) {
  asm volatile("mma.sync.aligned.m16n8k8.row.col.f32.bf16.bf16.f32 {%0,%1,%2,%3},{%4,%5},{%6},{%0,%1,%2,%3};"
               : "+f"(d[0]), "+f"(d[1]), "+f"(d[2]), "+f"(d[3]) : "r"(a0), "r"(0u), "r"(b0));
}
__device__ __forceinline__ uint32_t pack_bf16(float lo, float hi) {
  uint32_t r; asm("cvt.rn.bf16x2.f32 %0,%1,%2;" : "=r"(r) : "f"(hi), "f"(lo)); return r;
}
__device__ __forceinline__ float4 lds128f(uint32_t a) {
  float4 v; asm volatile("ld.shared.v4.f32 {%0,%1,%2,%3},[%4];" : "=f"(v.x), "=f"(v.y), "=f"(v.z), "=f"(v.w) : "r"(a) : "memory"); return v;
}
__device__ __forceinline__ uint4 lds128u(uint32_t a) {
  uint4 v; asm volatile("ld.shared.v4.u32 {%0,%1,%2,%3},[%4];" : "=r"(v.x), "=r"(v.y), "=r"(v.z), "=r"(v.w) : "r"(a) : "memory"); return v;
}
__device__ __forceinline__ float2 lds64f(uint32_t a) {
  float2 v; asm volatile("ld.shared.v2.f32 {%0,%1},[%2];" : "=f"(v.x), "=f"(v.y) : "r"(a) : "memory"); return v;
}
__device__ __forceinline__ uint2 lds64u(uint32_t a) {
  uint2 v; asm volatile("ld.shared.v2.u32 {%0,%1},[%2];" : "=r"(v.x), "=r"(v.y) : "r"(a) : "memory"); return v;
}
__device__ __forceinline__ void sts128f(uint32_t a, float x, float y, float z, float w) {
  asm volatile("st.shared.v4.f32 [%0],{%1,%2,%3,%4};" ::"r"(a), "f"(x), "f"(y), "f"(z), "f"(w) : "memory");
}
__device__ __forceinline__ void sts64f(uint32_t a, float x, float y) {
  asm volatile("st.shared.v2.f32 [%0],{%1,%2};" ::"r"(a), "f"(x), "f"(y) : "memory");
}
__device__ __forceinline__ void tma2d(uint32_t dst, const CUtensorMap* tm, int c0, int c1, uint32_t mb) {
  asm volatile("cp.async.bulk.tensor.2d.shared::cta.global.tile.mbarrier::complete_tx::bytes [%0],[%1,{%2,%3}],[%4];"
               ::"r"(dst), "l"(tm), "r"(c0), "r"(c1), "r"(mb) : "memory");
}
__device__ __forceinline__ uint32_t clock32() { uint32_t c; asm volatile("mov.u32 %0, %%clock;" : "=r"(c)); return c; }
__device__ __forceinline__ float ex2(float x) { float y; asm("ex2.approx.ftz.f32 %0,%1;" : "=f"(y) : "f"(x)); return y; }

__device__ __forceinline__ void tma2d_store(const CUtensorMap* tm, uint32_t src, int c0, int c1) {
  asm volatile("cp.async.bulk.tensor.2d.global.shared::cta.tile.bulk_group [%0,{%2,%3}],[%1];" ::"l"(tm), "r"(src), "r"(c0), "r"(c1) : "memory");
}
__device__ __forceinline__ void bulk_commit() { asm volatile("cp.async.bulk.commit_group;" ::: "memory"); }
__device__ __forceinline__ void bulk_wait_read0() { asm volatile("cp.async.bulk.wait_group.read 0;" ::: "memory"); }
__device__ __forceinline__ void bulk_wait0() { asm volatile("cp.async.bulk.wait_group 0;" ::: "memory"); }
__device__ __forceinline__ void fence_async_smem() { asm volatile("fence.proxy.async.shared::cta;" ::: "memory"); }
__device__ __forceinline__ void fence_async_all() { asm volatile("fence.proxy.async;" ::: "memory"); }
__device__ __forceinline__ void mbar_arrive(uint32_t a) { asm volatile("mbarrier.arrive.shared::cta.b64 _,[%0];" ::"r"(a) : "memory"); }
__device__ __forceinline__ void wg_fence() { asm volatile("wgmma.fence.sync.aligned;" ::: "memory"); }
__device__ __forceinline__ void wg_commit() { asm volatile("wgmma.commit_group.sync.aligned;" ::: "memory"); }
template <int N> __device__ __forceinline__ void wg_wait() { asm volatile("wgmma.wait_group.sync.aligned %0;" ::"n"(N) : "memory"); }
__device__ __forceinline__ uint64_t desc_k(uint32_t addr) {
  return (uint64_t)((addr & 0x3FFFF) >> 4) | ((uint64_t)1 << 16) | ((uint64_t)(1024 >> 4) << 32) | ((uint64_t)1 << 62);
}
__device__ __forceinline__ uint64_t desc_mn(uint32_t addr) {
  return (uint64_t)((addr & 0x3FFFF) >> 4) | ((uint64_t)(8192 >> 4) << 16) | ((uint64_t)(1024 >> 4) << 32) | ((uint64_t)1 << 62);
}
__device__ __forceinline__ void stsm4(uint32_t a, uint32_t r0, uint32_t r1, uint32_t r2, uint32_t r3) {
  asm volatile("stmatrix.sync.aligned.m8n8.x4.shared.b16 [%0],{%1,%2,%3,%4};" ::"r"(a), "r"(r0), "r"(r1), "r"(r2), "r"(r3) : "memory");
}
__device__ __forceinline__ unsigned ld_acquire(const unsigned* p) {
  unsigned v; asm volatile("ld.acquire.gpu.global.u32 %0,[%1];" : "=r"(v) : "l"(p) : "memory"); return v;
}
__device__ __forceinline__ void red_release(unsigned* p, unsigned v) {
  asm volatile("red.release.gpu.global.add.u32 [%0],%1;" ::"l"(p), "r"(v) : "memory");
}
__device__ __forceinline__ void wait_flag(const unsigned* p, unsigned target) {
  int n = 0;
  while (ld_acquire(p) < target) {
    __nanosleep(64);
    if (++n > (1 << 22)) __trap();
  }
}

__device__ __forceinline__ void bwait(uint32_t a, uint32_t ph) {
  asm volatile("{\n.reg .pred p;\n.reg .u32 n;\n"
               "mbarrier.try_wait.parity.shared::cta.b64 p,[%0],%1;\n@p bra.uni D;\nmov.u32 n,0;\n"
               "L: mbarrier.try_wait.parity.shared::cta.b64 p,[%0],%1;\n@p bra.uni D;\nadd.u32 n,n,1;\nsetp.lt.u32 p,n,4194304;\n@p bra.uni L;\ntrap;\n"
               "D:\n}" ::"r"(a), "r"(ph) : "memory");
}
__device__ __forceinline__ void arrive_if(bool c, uint32_t a) {
  asm volatile("{\n.reg .pred p;\nsetp.ne.u32 p,%1,0;\n@p mbarrier.arrive.shared::cta.b64 _,[%0];\n}" ::"r"(a), "r"((uint32_t)c) : "memory");
}
__device__ __forceinline__ void expect_if(bool c, uint32_t a, uint32_t tx) {
  asm volatile("{\n.reg .pred p;\nsetp.ne.u32 p,%2,0;\n@p mbarrier.arrive.expect_tx.shared::cta.b64 _,[%0],%1;\n}" ::"r"(a), "r"(tx), "r"((uint32_t)c) : "memory");
}
__device__ __forceinline__ void tma2d_if(bool c, uint32_t dst, const CUtensorMap* tm, int c0, int c1, uint32_t mb) {
  asm volatile("{\n.reg .pred p;\nsetp.ne.u32 p,%5,0;\n"
               "@p cp.async.bulk.tensor.2d.shared::cta.global.tile.mbarrier::complete_tx::bytes [%0],[%1,{%2,%3}],[%4];\n}"
               ::"r"(dst), "l"(tm), "r"(c0), "r"(c1), "r"(mb), "r"((uint32_t)c) : "memory");
}
__device__ __forceinline__ void publish_if(bool c, unsigned* flag) {
  asm volatile("{\n.reg .pred p;\nsetp.ne.u32 p,%1,0;\n@p cp.async.bulk.wait_group 0;\n@p fence.proxy.async;\n@p red.release.gpu.global.add.u32 [%0],1;\n}"
               ::"l"(flag), "r"((uint32_t)c) : "memory");
}

__device__ __forceinline__ void wgmma_n256(float (&d)[128], uint64_t da, uint64_t db, int scale_d) {
  asm volatile("{\n.reg .pred p;\nsetp.ne.b32 p, %130, 0;\n"
    "wgmma.mma_async.sync.aligned.m64n256k16.f32.bf16.bf16 {%0,%1,%2,%3,%4,%5,%6,%7,%8,%9,%10,%11,%12,%13,%14,%15,%16,%17,%18,%19,%20,%21,%22,%23,%24,%25,%26,%27,%28,%29,%30,%31,%32,%33,%34,%35,%36,%37,%38,%39,%40,%41,%42,%43,%44,%45,%46,%47,%48,%49,%50,%51,%52,%53,%54,%55,%56,%57,%58,%59,%60,%61,%62,%63,%64,%65,%66,%67,%68,%69,%70,%71,%72,%73,%74,%75,%76,%77,%78,%79,%80,%81,%82,%83,%84,%85,%86,%87,%88,%89,%90,%91,%92,%93,%94,%95,%96,%97,%98,%99,%100,%101,%102,%103,%104,%105,%106,%107,%108,%109,%110,%111,%112,%113,%114,%115,%116,%117,%118,%119,%120,%121,%122,%123,%124,%125,%126,%127}, %128, %129, p, 1, 1, 0, 1;\n}"
    : "+f"(d[0]), "+f"(d[1]), "+f"(d[2]), "+f"(d[3]), "+f"(d[4]), "+f"(d[5]), "+f"(d[6]), "+f"(d[7]), "+f"(d[8]), "+f"(d[9]), "+f"(d[10]), "+f"(d[11]), "+f"(d[12]), "+f"(d[13]), "+f"(d[14]), "+f"(d[15]), "+f"(d[16]), "+f"(d[17]), "+f"(d[18]), "+f"(d[19]), "+f"(d[20]), "+f"(d[21]), "+f"(d[22]), "+f"(d[23]), "+f"(d[24]), "+f"(d[25]), "+f"(d[26]), "+f"(d[27]), "+f"(d[28]), "+f"(d[29]), "+f"(d[30]), "+f"(d[31]), "+f"(d[32]), "+f"(d[33]), "+f"(d[34]), "+f"(d[35]), "+f"(d[36]), "+f"(d[37]), "+f"(d[38]), "+f"(d[39]), "+f"(d[40]), "+f"(d[41]), "+f"(d[42]), "+f"(d[43]), "+f"(d[44]), "+f"(d[45]), "+f"(d[46]), "+f"(d[47]), "+f"(d[48]), "+f"(d[49]), "+f"(d[50]), "+f"(d[51]), "+f"(d[52]), "+f"(d[53]), "+f"(d[54]), "+f"(d[55]), "+f"(d[56]), "+f"(d[57]), "+f"(d[58]), "+f"(d[59]), "+f"(d[60]), "+f"(d[61]), "+f"(d[62]), "+f"(d[63]), "+f"(d[64]), "+f"(d[65]), "+f"(d[66]), "+f"(d[67]), "+f"(d[68]), "+f"(d[69]), "+f"(d[70]), "+f"(d[71]), "+f"(d[72]), "+f"(d[73]), "+f"(d[74]), "+f"(d[75]), "+f"(d[76]), "+f"(d[77]), "+f"(d[78]), "+f"(d[79]), "+f"(d[80]), "+f"(d[81]), "+f"(d[82]), "+f"(d[83]), "+f"(d[84]), "+f"(d[85]), "+f"(d[86]), "+f"(d[87]), "+f"(d[88]), "+f"(d[89]), "+f"(d[90]), "+f"(d[91]), "+f"(d[92]), "+f"(d[93]), "+f"(d[94]), "+f"(d[95]), "+f"(d[96]), "+f"(d[97]), "+f"(d[98]), "+f"(d[99]), "+f"(d[100]), "+f"(d[101]), "+f"(d[102]), "+f"(d[103]), "+f"(d[104]), "+f"(d[105]), "+f"(d[106]), "+f"(d[107]), "+f"(d[108]), "+f"(d[109]), "+f"(d[110]), "+f"(d[111]), "+f"(d[112]), "+f"(d[113]), "+f"(d[114]), "+f"(d[115]), "+f"(d[116]), "+f"(d[117]), "+f"(d[118]), "+f"(d[119]), "+f"(d[120]), "+f"(d[121]), "+f"(d[122]), "+f"(d[123]), "+f"(d[124]), "+f"(d[125]), "+f"(d[126]), "+f"(d[127])
    : "l"(da), "l"(db), "r"(scale_d));
}
__device__ __forceinline__ void wgmma_n128(float (&d)[64], uint64_t da, uint64_t db, int scale_d) {
  asm volatile("{\n.reg .pred p;\nsetp.ne.b32 p, %66, 0;\n"
    "wgmma.mma_async.sync.aligned.m64n128k16.f32.bf16.bf16 {%0,%1,%2,%3,%4,%5,%6,%7,%8,%9,%10,%11,%12,%13,%14,%15,%16,%17,%18,%19,%20,%21,%22,%23,%24,%25,%26,%27,%28,%29,%30,%31,%32,%33,%34,%35,%36,%37,%38,%39,%40,%41,%42,%43,%44,%45,%46,%47,%48,%49,%50,%51,%52,%53,%54,%55,%56,%57,%58,%59,%60,%61,%62,%63}, %64, %65, p, 1, 1, 0, 1;\n}"
    : "+f"(d[0]), "+f"(d[1]), "+f"(d[2]), "+f"(d[3]), "+f"(d[4]), "+f"(d[5]), "+f"(d[6]), "+f"(d[7]), "+f"(d[8]), "+f"(d[9]), "+f"(d[10]), "+f"(d[11]), "+f"(d[12]), "+f"(d[13]), "+f"(d[14]), "+f"(d[15]), "+f"(d[16]), "+f"(d[17]), "+f"(d[18]), "+f"(d[19]), "+f"(d[20]), "+f"(d[21]), "+f"(d[22]), "+f"(d[23]), "+f"(d[24]), "+f"(d[25]), "+f"(d[26]), "+f"(d[27]), "+f"(d[28]), "+f"(d[29]), "+f"(d[30]), "+f"(d[31]), "+f"(d[32]), "+f"(d[33]), "+f"(d[34]), "+f"(d[35]), "+f"(d[36]), "+f"(d[37]), "+f"(d[38]), "+f"(d[39]), "+f"(d[40]), "+f"(d[41]), "+f"(d[42]), "+f"(d[43]), "+f"(d[44]), "+f"(d[45]), "+f"(d[46]), "+f"(d[47]), "+f"(d[48]), "+f"(d[49]), "+f"(d[50]), "+f"(d[51]), "+f"(d[52]), "+f"(d[53]), "+f"(d[54]), "+f"(d[55]), "+f"(d[56]), "+f"(d[57]), "+f"(d[58]), "+f"(d[59]), "+f"(d[60]), "+f"(d[61]), "+f"(d[62]), "+f"(d[63])
    : "l"(da), "l"(db), "r"(scale_d));
}
namespace chain {
constexpr uint32_t OFF_A = 0;
constexpr uint32_t OFF_B = 81920;
constexpr uint32_t OFF_KX = 163840;
constexpr uint32_t OFF_MEM = 180224;
constexpr uint32_t OFF_O = 190464;
constexpr uint32_t OFF_QS = 198656;
constexpr uint32_t OFF_KS = 199680;
constexpr uint32_t OFF_VS = 201728;
constexpr uint32_t OFF_XB = 203776;
constexpr uint32_t OFF_XQ = 207872;
constexpr uint32_t OFF_SL = 209920;
constexpr uint32_t OFF_SR = 211200;
constexpr uint32_t OFF_RB = 212480;
constexpr uint32_t OFF_EXP = 214016;
constexpr uint32_t OFF_ZERO = 216064;
constexpr uint32_t OFF_BAR = 218624;
constexpr uint32_t OFF_PROF = OFF_BAR + 256;
constexpr uint32_t SMEM_BYTES = OFF_PROF + 1024;
static_assert(OFF_O % 1024 == 0 && OFF_BAR % 256 == 0, "alignment");
constexpr int B_MEM = 0, B_O = 8, B_PAIR = 16, B_TOK = 17, B_W = 19, NBAR = 24;
#define RING 10
#define POLL_DELAY 300

#define PROF(i)

__device__ __forceinline__ void bprobe(uint32_t a, uint32_t ph) {
  asm volatile("mbarrier.test_wait.parity.shared::cta.b64 pq,[%0],%1;" ::"r"(a), "r"(ph) : "memory");
}
__device__ __forceinline__ void bwait_q(uint32_t a, uint32_t ph) {
  asm volatile("{\n.reg .pred p;\n.reg .u32 n;\n@pq bra.uni D;\nmov.u32 n,0;\n"
               "L: mbarrier.try_wait.parity.shared::cta.b64 p,[%0],%1;\n@p bra.uni D;\nadd.u32 n,n,1;\nsetp.lt.u32 p,n,4194304;\n@p bra.uni L;\ntrap;\n"
               "D:\n}" ::"r"(a), "r"(ph) : "memory");
}
template <int P> __device__ __forceinline__ void twait(uint32_t a, uint32_t ph) {
  if (P == 0) asm volatile("mbarrier.try_wait.parity.shared::cta.b64 pw0,[%0],%1;" ::"r"(a), "r"(ph) : "memory");
  else if (P == 1) asm volatile("mbarrier.try_wait.parity.shared::cta.b64 pw1,[%0],%1;" ::"r"(a), "r"(ph) : "memory");
  else asm volatile("mbarrier.try_wait.parity.shared::cta.b64 pw2,[%0],%1;" ::"r"(a), "r"(ph) : "memory");
}
template <int P> __device__ __forceinline__ uint32_t gate(uint32_t a, uint32_t alt) {
  uint32_t r;
  if (P == 0) asm volatile("selp.u32 %0,%1,%2,pw0;\nand.pred pall, pall, pw0;" : "=r"(r) : "r"(a), "r"(alt));
  else if (P == 1) asm volatile("selp.u32 %0,%1,%2,pw1;\nand.pred pall, pall, pw1;" : "=r"(r) : "r"(a), "r"(alt));
  else asm volatile("selp.u32 %0,%1,%2,pw2;\nand.pred pall, pall, pw2;" : "=r"(r) : "r"(a), "r"(alt));
  return r;
}
template <int NP> __device__ __forceinline__ void twait_n(int n, uint32_t a, uint32_t ph) {
  if (n % NP == 0) twait<0>(a, ph); else if (n % NP == 1) twait<1>(a, ph); else twait<2>(a, ph);
}
template <int NP> __device__ __forceinline__ uint32_t gate_n(int n, uint32_t a, uint32_t alt) {
  return n % NP == 0 ? gate<0>(a, alt) : (n % NP == 1 ? gate<1>(a, alt) : gate<2>(a, alt));
}
constexpr int WDEPTH = 1;
__device__ __forceinline__ void pall_set() { asm volatile("setp.eq.u32 pall, 0, 0;"); }
__device__ __forceinline__ bool pall_get() { uint32_t r; asm volatile("selp.u32 %0,1,0,pall;" : "=r"(r)); return r != 0; }
__device__ __forceinline__ uint32_t junk() { uint32_t j; asm volatile("" : "=r"(j)); return j; }
__device__ __forceinline__ void mma_top(float (&d)[4], uint32_t a0, uint32_t a2, uint32_t b0, uint32_t b1) {
  const uint32_t j1 = junk(), j3 = junk();
  asm volatile("mma.sync.aligned.m16n8k16.row.col.f32.bf16.bf16.f32 {%0,%1,%2,%3},{%4,%5,%6,%7},{%8,%9},{%0,%1,%2,%3};"
               : "+f"(d[0]), "+f"(d[1]), "+f"(d[2]), "+f"(d[3]) : "r"(a0), "r"(j1), "r"(a2), "r"(j3), "r"(b0), "r"(b1));
}
__device__ __forceinline__ void mma_top8(float (&d)[4], uint32_t a0, uint32_t b0) {
  const uint32_t j1 = junk();
  asm volatile("mma.sync.aligned.m16n8k8.row.col.f32.bf16.bf16.f32 {%0,%1,%2,%3},{%4,%5},{%6},{%0,%1,%2,%3};"
               : "+f"(d[0]), "+f"(d[1]), "+f"(d[2]), "+f"(d[3]) : "r"(a0), "r"(j1), "r"(b0));
}
__device__ __forceinline__ void mbar_expect_cnt(uint32_t a, uint32_t tx) { mbar_expect(a, tx); }

template <int KH> struct KMap {
  static constexpr __host__ __device__ int first(int j) { return KH == 0 ? 0 : ((j & 1) ? 2 : 3); }
  static constexpr __host__ __device__ int count(int j) { return KH == 0 ? ((j & 1) ? 2 : 3) : ((j & 1) ? 3 : 2); }
  static constexpr __host__ __device__ int base(int j) { return (j >> 1) * 5 + ((j & 1) ? count(0) : 0); }
  static constexpr __host__ __device__ int slot(int t) { int j = 0; while (j < 7 && base(j + 1) <= t) j++; return j; }
  static constexpr __host__ __device__ int kstep(int t) { return first(slot(t)) + t - base(slot(t)); }
  static constexpr __host__ __device__ uint32_t off(int t) { return (uint32_t)(slot(t) * 10240 + kstep(t) * 2048); }
};
template <int KH, int N>
__device__ __forceinline__ void load_tiles(uint32_t (&w)[N][4], uint32_t base) {
#pragma unroll
  for (int t = 0; t < N; t++) ldsm4t(w[t], base + KMap<KH>::off(t));
}

template <int KH>
__device__ __forceinline__ void phase_q(const uint32_t (&wq)[20][4], const uint32_t (&wk)[20][4], uint32_t (&dyn)[RING][4],
                                        float (&aq)[4], float (&ak)[4], float (&av)[4], uint32_t l16, uint32_t bar, uint32_t vbase, int s
                                        ) {
#pragma unroll
  for (int i = 0; i < 4; i++) aq[i] = ak[i] = av[i] = 0.f;
  uint32_t b[2][6];
  const uint32_t par = (s - 1) & 1;
  pall_set();
#pragma unroll
  for (int n = 0; n < WDEPTH; n++) twait_n<WDEPTH + 1>(n, bar + (B_MEM + n) * 8, par);
#pragma unroll
  for (int j = -1; j < 8; j++) {
    if (j < 7) {
      const int n = j + 1;
      const uint32_t a = gate_n<WDEPTH + 1>(n, l16, bar - OFF_BAR) + OFF_MEM + n * 1280 + KMap<KH>::first(n) * 256;
      uint32_t t4[4];
      ldsm4(t4, a);
      b[n & 1][0] = t4[0]; b[n & 1][1] = t4[1]; b[n & 1][2] = t4[2]; b[n & 1][3] = t4[3];
      if (KMap<KH>::count(n) == 3) ldsm2(b[n & 1][4], b[n & 1][5], a + 512);
      if (n + WDEPTH < 8) twait_n<WDEPTH + 1>(n + WDEPTH, bar + (B_MEM + n + WDEPTH) * 8, par);
    }
    if (j >= 0) {
      const int p = j & 1;
#pragma unroll
      for (int i = 0; i < KMap<KH>::count(j); i++) {
        const int t = KMap<KH>::base(j) + i;
        mma16816(aq, wq[t], b[p][2 * i], b[p][2 * i + 1]);
        mma16816(ak, wk[t], b[p][2 * i], b[p][2 * i + 1]);
        mma16816(av, dyn[t % RING], b[p][2 * i], b[p][2 * i + 1]);
        if (t + RING < 20) ldsm4t(dyn[t % RING], vbase + KMap<KH>::off(t + RING));
      }
    }
  }
  if (!pall_get()) {
#pragma unroll 1
    for (int j = 0; j < 8; j++) mbar_wait(bar + (B_MEM + j) * 8, par);
#pragma unroll
    for (int i = 0; i < 4; i++) aq[i] = ak[i] = av[i] = 0.f;
#pragma unroll
    for (int t = 0; t < 20; t++) {
      uint32_t b0, b1, a[4];
      ldsm2(b0, b1, l16 + OFF_MEM + KMap<KH>::slot(t) * 1280 + KMap<KH>::kstep(t) * 256);
      ldsm4t(a, vbase + KMap<KH>::off(t));
      mma16816(aq, wq[t], b0, b1);
      mma16816(ak, wk[t], b0, b1);
      mma16816(av, a, b0, b1);
    }
  }
}

__device__ __forceinline__ void glob_red(const float (&c)[4], int idx) {
  asm volatile("red.relaxed.gpu.global.add.v4.f32 [%0],{%1,%2,%3,%4};" ::"l"(g_acc4 + idx * 4), "f"(c[0]), "f"(c[1]), "f"(c[2]), "f"(1.0f) : "memory");
  asm volatile("red.relaxed.gpu.global.add.v2.f32 [%0],{%1,%2};" ::"l"(g_acc2 + idx * 2), "f"(c[3]), "f"(1.0f) : "memory");
}
__device__ __forceinline__ void glob_poll(uint32_t t_start, int idx, uint32_t dst, uint32_t bar
) {
  const float* p4 = g_acc4 + idx * 4;
  const float* p2 = g_acc2 + idx * 2;
  while (clock32() - t_start < (uint32_t)POLL_DELAY) {}
  float a0, a1, a2, an, b0, bn;
  int n = 0;
  while (true) {
    asm volatile("ld.relaxed.gpu.global.v4.f32 {%0,%1,%2,%3},[%4];" : "=f"(a0), "=f"(a1), "=f"(a2), "=f"(an) : "l"(p4) : "memory");
    asm volatile("ld.relaxed.gpu.global.v2.f32 {%0,%1},[%2];" : "=f"(b0), "=f"(bn) : "l"(p2) : "memory");
    ++n;
    if (__all_sync(0xffffffffu, an >= 8.0f && bn >= 8.0f)) break;
    if (n > SPIN_LIMIT) __trap();
  }
  const uint32_t t0 = movm(pack_bf16(a0, a1)), t1 = movm(pack_bf16(a2, b0));
#pragma unroll
  for (int d = 0; d < 8; d++) {
    const uint32_t ra = (dst ^ (d << 24)) + d * 1280, rb = (bar ^ (d << 24)) + (B_MEM + d) * 8;
    st_async_b32(ra, t0, rb);
    st_async_b32(ra + 128, t1, rb);
  }
}

__device__ __forceinline__ void chain_role(const CUtensorMap& tmWq, const CUtensorMap& tmWk, const CUtensorMap& tmWv,
                                           const CUtensorMap& tmWo, const CUtensorMap& tmWo4, const CUtensorMap& tmKV, const CUtensorMap& tmKVM,
                                           const bf16* __restrict__ mem0, uint8_t* smem_raw) {
  asm volatile(".reg .pred pq, pw0, pw1, pw2, pall;");
  uint32_t rank_u; asm("mov.u32 %0, %%cluster_ctarank;" : "=r"(rank_u));
  const int rank = (int)rank_u;
  const uint32_t sb = mapa((smem_u32(smem_raw) + 1023) & ~1023u, rank_u);
  const int tid = threadIdx.x;
  int lane; asm volatile("mov.u32 %0, %%laneid;" : "=r"(lane));
  const int warp = __shfl_sync(0xffffffffu, tid >> 5, 0);
  const int cl = blockIdx.x >> 3;
  const int head = cl * 4 + (rank >> 1), hf = rank & 1;
  const int col0 = head * 128 + hf * 64;
  const int pw = warp & 3;
  const uint32_t bar = sb + OFF_BAR;

  if (tid == 0) {
    for (int i = 0; i < NBAR; i++) mbar_init(bar + i * 8, 1);
    asm volatile("fence.mbarrier_init.release.cluster;" ::: "memory");
    asm volatile("fence.proxy.async.shared::cta;" ::: "memory");
    mbar_expect(bar + (B_W + 0) * 8, 81920);
    for (int j = 0; j < 8; j++) tma2d(sb + OFF_A + j * 10240, &tmWq, col0, (rank ^ j) * 80, bar + (B_W + 0) * 8);
    mbar_expect(bar + (B_W + 1) * 8, 81920);
    for (int j = 0; j < 8; j++) tma2d(sb + OFF_B + j * 10240, &tmWk, col0, (rank ^ j) * 80, bar + (B_W + 1) * 8);
    for (int j = 0; j < 8; j++) { mbar_expect(bar + (B_MEM + j) * 8, 1280); mbar_expect(bar + (B_O + j) * 8, 1024); }
    mbar_expect(bar + B_PAIR * 8, 1280);
  }
  if (tid < 160) asm volatile("st.shared.v4.u32 [%0],{%1,%1,%1,%1};" ::"r"(sb + OFF_ZERO + tid * 16), "r"(0) : "memory");
  fence_async_smem();
  for (int p = tid; p < 640; p += 256) {
    const int i = p / 80, ch = p % 80, j = ch / 10, c = ch % 10;
    const uint4 v = *reinterpret_cast<const uint4*>(mem0 + i * 640 + (rank ^ j) * 80 + c * 8);
    asm volatile("st.shared.v4.u32 [%0],{%1,%2,%3,%4};" ::"r"(sb + OFF_MEM + ch * 128 + i * 16), "r"(v.x), "r"(v.y), "r"(v.z), "r"(v.w) : "memory");
  }
  __syncthreads();
  asm volatile("barrier.cluster.arrive.release.aligned;" ::: "memory");

  const int q4 = lane >> 3, rr = lane & 7;
  const uint32_t lp = sb + ((q4 >> 1) * 8 + rr) * 128 + (((2 * pw + (q4 & 1)) ^ rr) << 4);
  const uint32_t l16 = sb + lane * 16, l8 = sb + lane * 8;

  uint32_t wq[20][4], wk[20][4];
  mbar_wait(bar + (B_W + 0) * 8, 0);
  if (warp < 4) load_tiles<0, 20>(wq, lp + OFF_A); else load_tiles<1, 20>(wq, lp + OFF_A);
  __syncthreads();
  if (tid == 0) {
    mbar_expect(bar + (B_W + 3) * 8, 81920);
    for (int j = 0; j < 8; j++) tma2d(sb + OFF_A + j * 10240, &tmWv, col0, (rank ^ j) * 80, bar + (B_W + 3) * 8);
  }
  mbar_wait(bar + (B_W + 1) * 8, 0);
  if (warp < 4) load_tiles<0, 20>(wk, lp + OFF_B); else load_tiles<1, 20>(wk, lp + OFF_B);
  __syncthreads();
  if (tid == 0) {
    mbar_expect(bar + (B_W + 4) * 8, 65536);
    for (int j = 0; j < 8; j++) tma2d(sb + OFF_B + j * 8192, &tmWo, rank * 80, cl * 512 + (rank ^ j) * 64, bar + (B_W + 4) * 8);
    mbar_expect(bar + (B_W + 2) * 8, 16384);
    for (int j = 0; j < 8; j++) tma2d(sb + OFF_B + 65536 + j * 2048, &tmWo4, rank * 80 + 64, cl * 512 + (rank ^ j) * 64, bar + (B_W + 2) * 8);
  }
  asm volatile("barrier.cluster.wait.acquire.aligned;" ::: "memory");

  if (warp < 4) {
    uint32_t dyn[RING][4];
    mbar_wait(bar + (B_W + 3) * 8, 0);
    mbar_wait(bar + (B_W + 4) * 8, 0);
    load_tiles<0, RING>(dyn, lp + OFF_A);

    for (int s = 0; s < NSEG; s++) {
      PROF(0);
      const int par = s & 1;
      float aq[4], ak[4], av[4];
      phase_q<0>(wq, wk, dyn, aq, ak, av, l16, bar, lp + OFF_A, s
      );
      PROF(1);
      sts128f(l16 + OFF_XB + pw * 1024, ak[0], ak[1], ak[2], ak[3]);
      sts128f(l16 + OFF_XB + pw * 1024 + 512, av[0], av[1], av[2], av[3]);
      bar_sync(1 + pw, 64);
      {
        const float4 o = lds128f(l16 + OFF_XQ + pw * 512);
        stsm2t(sb + (lane & 15) * 16 + OFF_QS + 2 * pw * 128, pack_bf16(aq[0] + o.x, aq[1] + o.y), pack_bf16(aq[2] + o.z, aq[3] + o.w));
      }
      bar_sync(0, 256);
      PROF(2);
      if (s == NSEG - 1) break;
      if (pw == 0) {
        uint32_t qa[4][4], km[2][4];
        const uint32_t qadr = sb + OFF_QS + (lane >> 4) * 128 + (lane & 7) * 16;
#pragma unroll
        for (int k = 0; k < 4; k++) ldsm4(qa[k], qadr + k * 256);
        ldsm4(km[0], l16 + OFF_KS + par * 1024);
        ldsm4(km[1], l16 + OFF_KS + par * 1024 + 512);
        float m0[4] = {0.f, 0.f, 0.f, 0.f}, m1[4] = {0.f, 0.f, 0.f, 0.f};
        mma16816(m0, qa[0], km[0][0], km[0][1]);
        mma16816(m1, qa[2], km[1][0], km[1][1]);
        mma16816(m0, qa[1], km[0][2], km[0][3]);
        mma16816(m1, qa[3], km[1][2], km[1][3]);
        const float mx = m0[0] + m1[0], my = m0[1] + m1[1];
        st_async_v2((l8 + OFF_SR) ^ (1 << 24), __float_as_uint(mx), __float_as_uint(my), (bar + B_PAIR * 8) ^ (1 << 24));
        sts64f(l8 + OFF_SL, mx, my);
        PROF(10);
        bar_arrive(5, 160);
      }
      bar_sync(6, 256);
#pragma unroll
      for (int t = 0; t < RING; t++) ldsm4t(dyn[t], lp + OFF_B + t * 2048);
      PROF(3);
      float c0[4] = {0.f, 0.f, 0.f, 0.f}, c1[4] = {0.f, 0.f, 0.f, 0.f};
      {
        uint32_t b[2][2][4];
        pall_set();
#pragma unroll
        for (int n = 0; n < WDEPTH; n++) twait_n<WDEPTH + 1>(n, bar + (B_O + n) * 8, par);
#pragma unroll
        for (int j = -1; j < 8; j++) {
          if (j < 7) {
            const int n = j + 1;
            const uint32_t a = gate_n<WDEPTH + 1>(n, l16, bar - OFF_BAR) + OFF_O + n * 1024;
            ldsm4(b[n & 1][0], a); ldsm4(b[n & 1][1], a + 512);
            if (n == 0) PROF(4);
            if (n + WDEPTH < 8) twait_n<WDEPTH + 1>(n + WDEPTH, bar + (B_O + n + WDEPTH) * 8, par);
          }
          if (j >= 0) {
            const int p = j & 1;
#pragma unroll
            for (int k = 0; k < 4; k++) {
              const int t = 4 * j + k;
              if (k & 1) mma16816(c1, dyn[t % RING], b[p][k >> 1][2], b[p][k >> 1][3]); else mma16816(c0, dyn[t % RING], b[p][k >> 1][0], b[p][k >> 1][1]);
              if (t + RING < 32) ldsm4t(dyn[t % RING], lp + OFF_B + (t + RING) * 2048);
            }
          }
        }
        if (!pall_get()) {
#pragma unroll 1
          for (int j = 0; j < 8; j++) mbar_wait(bar + (B_O + j) * 8, par);
#pragma unroll
          for (int i = 0; i < 4; i++) c0[i] = c1[i] = 0.f;
#pragma unroll 1
          for (int t = 0; t < 32; t++) {
            uint32_t b0, b1, a[4];
            ldsm2(b0, b1, l16 + OFF_O + t * 256);
            ldsm4t(a, lp + OFF_B + t * 2048);
            mma16816(c0, a, b0, b1);
          }
        }
      }
      PROF(5);
      bar_arrive(9, 224);
#pragma unroll
      for (int i = 0; i < 4; i++) c0[i] += c1[i];
      const int idx = ((s & 7) * 8 + rank) * 160 + pw * 32 + lane;
      glob_red(c0, idx);
      const uint32_t t_start = clock32();
      load_tiles<0, RING>(dyn, lp + OFF_A);
      glob_poll(t_start, idx, sb + OFF_MEM + pw * 256 + lane * 4, bar
      );
      PROF(6);
    }
  } else {
    uint32_t dyn[RING][4];
    mbar_wait(bar + (B_W + 3) * 8, 0);
    mbar_wait(bar + (B_W + 2) * 8, 0);
    load_tiles<1, RING>(dyn, lp + OFF_A);
    if (warp == 5 && lane == 0) {
      wait_flag(&g_flags.kv[0], 64);
      fence_async_all();
      for (int i = 0; i < 2; i++) {
        mbar_expect(bar + (B_TOK + i) * 8, 8192);
        tma2d(sb + OFF_KX + i * 8192, &tmKV, col0, i * 32, bar + (B_TOK + i) * 8);
        tma2d(sb + OFF_KX + i * 8192 + 4096, &tmKV, 4096 + col0, i * 32, bar + (B_TOK + i) * 8);
      }
    }
    const float sl2 = 0.08838834764831845f * 1.4426950408889634f;

    for (int s = 0; s < NSEG; s++) {
      PROF(0);
      const int par = s & 1;
      const bool last = (s == NSEG - 1);
      float aq[4], ak[4], av[4];
      phase_q<1>(wq, wk, dyn, aq, ak, av, l16, bar, lp + OFF_A, s
      );
      PROF(1);
      sts128f(l16 + OFF_XQ + pw * 512, aq[0], aq[1], aq[2], aq[3]);
      const uint32_t kxb = sb + OFF_KX + par * 8192;
      uint32_t kx[2][4];
      if (!last) {
        bwait(bar + (B_TOK + par) * 8, (s >> 1) & 1);
        const uint32_t ka = kxb + (pw * 8 + rr) * 128;
        ldsm4(kx[0], ka + ((q4 ^ rr) << 4));
        ldsm4(kx[1], ka + (((4 + q4) ^ rr) << 4));
      }
      bar_sync(1 + pw, 64);
      uint32_t vm0, vm1;
      {
        const float4 o = lds128f(l16 + OFF_XB + pw * 1024), u = lds128f(l16 + OFF_XB + pw * 1024 + 512);
        stsm2t(sb + (lane & 15) * 16 + OFF_KS + par * 1024 + 2 * pw * 128, pack_bf16(ak[0] + o.x, ak[1] + o.y), pack_bf16(ak[2] + o.z, ak[3] + o.w));
        vm0 = pack_bf16(av[0] + u.x, av[1] + u.y);
        vm1 = pack_bf16(av[2] + u.z, av[3] + u.w);
      }
      bar_sync(0, 256);
      PROF(2);
      if (!last) {
        float sc[5][2];
        uint32_t vx[2][4];
        {
          uint32_t qa[4][4];
          const uint32_t qadr = sb + OFF_QS + (lane >> 4) * 128 + (lane & 7) * 16;
#pragma unroll
          for (int k = 0; k < 4; k++) ldsm4(qa[k], qadr + k * 256);
          float t0[4] = {0.f, 0.f, 0.f, 0.f}, t1[4] = {0.f, 0.f, 0.f, 0.f};
          mma16816(t0, qa[0], kx[0][0], kx[0][1]);
          mma16816(t1, qa[2], kx[1][0], kx[1][1]);
          mma16816(t0, qa[1], kx[0][2], kx[0][3]);
          mma16816(t1, qa[3], kx[1][2], kx[1][3]);
          const float tx = t0[0] + t1[0], ty = t0[1] + t1[1];
          st_async_v2((l8 + OFF_SR + (pw + 1) * 256) ^ (1 << 24), __float_as_uint(tx), __float_as_uint(ty), (bar + B_PAIR * 8) ^ (1 << 24));
          sts64f(l8 + OFF_SL + (pw + 1) * 256, tx, ty);
        }
        PROF(10);
        bar_arrive(6, 256);
        if (warp == 6 && lane < 8 && s > 0) mbar_expect(bar + (B_MEM + lane) * 8, 1280);
        {
          const uint32_t va = kxb + 4096 + lane * 128;
          ldsm4t(vx[0], va + (((2 * pw) ^ rr) << 4));
          ldsm4t(vx[1], va + (((2 * pw + 1) ^ rr) << 4));
        }
        bar_sync(5, 160);
#pragma unroll
        for (int n = 0; n < 5; n++) { const float2 v = lds64f(l8 + OFF_SL + n * 256); sc[n][0] = v.x; sc[n][1] = v.y; }
        PROF(3);
        bwait(bar + B_PAIR * 8, par);
        PROF(4);
#pragma unroll
        for (int n = 0; n < 5; n++) { const float2 v = lds64f(l8 + OFF_SR + n * 256); sc[n][0] += v.x; sc[n][1] += v.y; }
        float mxv = fmaxf(fmaxf(fmaxf(sc[0][0], sc[0][1]), fmaxf(sc[1][0], sc[1][1])), fmaxf(fmaxf(sc[2][0], sc[2][1]), fmaxf(sc[3][0], sc[3][1])));
        mxv = fmaxf(mxv, fmaxf(sc[4][0], sc[4][1]));
        mxv = fmaxf(mxv, __shfl_xor_sync(0xffffffffu, mxv, 1));
        mxv = fmaxf(mxv, __shfl_xor_sync(0xffffffffu, mxv, 2));
        const float off = -mxv * sl2;
        uint32_t p[5];
        float sum = 0.f;
#pragma unroll
        for (int n = 0; n < 5; n++) {
          const float e0 = ex2(fmaf(sc[n][0], sl2, off)), e1 = ex2(fmaf(sc[n][1], sl2, off));
          p[n] = pack_bf16(e0, e1);
          sum += e0 + e1;
        }
        PROF(5);
        float o0[4] = {0.f, 0.f, 0.f, 0.f}, o1[4] = {0.f, 0.f, 0.f, 0.f};
        mma_top(o0, p[0], p[1], vm0, vx[0][0]);
        mma_top(o1, p[0], p[1], vm1, vx[1][0]);
        mma_top(o0, p[2], p[3], vx[0][1], vx[0][2]);
        mma_top(o1, p[2], p[3], vx[1][1], vx[1][2]);
        mma_top8(o0, p[4], vx[0][3]);
        mma_top8(o1, p[4], vx[1][3]);
        sum += __shfl_xor_sync(0xffffffffu, sum, 1);
        sum += __shfl_xor_sync(0xffffffffu, sum, 2);
        float inv; asm("rcp.approx.ftz.f32 %0,%1;" : "=f"(inv) : "f"(sum));
        const uint32_t ob0 = pack_bf16(o0[0] * inv, o0[1] * inv), ob1 = pack_bf16(o1[0] * inv, o1[1] * inv);
        const uint32_t dst = sb + lane * 4 + OFF_O + pw * 256, ob = bar + B_O * 8;
#pragma unroll
        for (int d = 0; d < 8; d++) {
          const uint32_t ra = (dst ^ (d << 24)) + d * 1024, rb = ob ^ (d * 8 | d << 24);
          st_async_b32(ra, ob0, rb);
          st_async_b32(ra + 128, ob1, rb);
        }
        {
          const int r8 = (q4 >> 1) * 8 + rr;
          const uint32_t o4 = sb + OFF_B + 65536 + (2 * pw * 64 + r8) * 32 + (((q4 & 1) ^ ((rr >> 2) & 1)) << 4);
#pragma unroll
          for (int t = 0; t < 8; t++) ldsm4t(dyn[t], o4 + ((t >> 2) * 64 + 16 * (t & 3)) * 32);
        }
        if (warp == 6 && lane == 0) mbar_expect(bar + B_PAIR * 8, 1280);
      }
      PROF(7);
      stsm2t(sb + (lane & 15) * 16 + OFF_VS + par * 1024 + 2 * pw * 128, vm0, vm1);
      bar_sync(7, 128);
      if (!last) {
        float c0[4] = {0.f, 0.f, 0.f, 0.f}, c1[4] = {0.f, 0.f, 0.f, 0.f};
#pragma unroll
        for (int jj = 0; jj < 2; jj++) {
          const uint32_t joff = (2 * pw + jj) * 1024;
          bwait(bar + (B_O + 2 * pw + jj) * 8, par);
          uint32_t b[2][4];
          ldsm4(b[0], l16 + OFF_O + joff);
          ldsm4(b[1], l16 + OFF_O + joff + 512);
          mma16816(c0, dyn[4 * jj], b[0][0], b[0][1]); mma16816(c1, dyn[4 * jj + 1], b[0][2], b[0][3]);
          mma16816(c0, dyn[4 * jj + 2], b[1][0], b[1][1]); mma16816(c1, dyn[4 * jj + 3], b[1][2], b[1][3]);
        }
#pragma unroll
        for (int i = 0; i < 4; i++) c0[i] += c1[i];
        if (pw < 3) {
          sts128f(l16 + OFF_RB + pw * 512, c0[0], c0[1], c0[2], c0[3]);
          bar_arrive(8, 128);
          bar_sync(9, 224);
          load_tiles<1, RING>(dyn, lp + OFF_A);
        } else {
          bar_sync(8, 128);
          const float4 r0 = lds128f(l16 + OFF_RB), r1 = lds128f(l16 + OFF_RB + 512), r2 = lds128f(l16 + OFF_RB + 1024);
          c0[0] += (r0.x + r1.x) + r2.x; c0[1] += (r0.y + r1.y) + r2.y; c0[2] += (r0.z + r1.z) + r2.z; c0[3] += (r0.w + r1.w) + r2.w;
          PROF(8);
          const int idx = ((s & 7) * 8 + rank) * 160 + 128 + lane;
          glob_red(c0, idx);
          const uint32_t t_start = clock32();
          load_tiles<1, RING>(dyn, lp + OFF_A);
          glob_poll(t_start, idx, sb + OFF_MEM + 4 * 256 + lane * 4, bar
      );
          PROF(9);
        }
      }
      if (pw == 0) {
        if (lane == 0 && s > 0) {
          bulk_wait0();
          asm volatile("red.relaxed.gpu.global.add.u32 [%0],1;" ::"l"(&g_flags.mem[s - 1]) : "memory");
        }
        __syncwarp();
#pragma unroll
        for (int it = 0; it < 2; it++) {
          const int j = lane & 7, ch = it * 4 + (lane >> 3);
          const uint4 kv = lds128u(sb + OFF_KS + par * 1024 + ch * 128 + j * 16);
          const uint4 vv = lds128u(sb + OFF_VS + par * 1024 + ch * 128 + j * 16);
          const uint32_t dst = sb + OFF_EXP + j * 128 + ((ch ^ j) << 4);
          asm volatile("st.shared.v4.u32 [%0],{%1,%2,%3,%4};" ::"r"(dst), "r"(kv.x), "r"(kv.y), "r"(kv.z), "r"(kv.w) : "memory");
          asm volatile("st.shared.v4.u32 [%0],{%1,%2,%3,%4};" ::"r"(dst + 1024), "r"(vv.x), "r"(vv.y), "r"(vv.z), "r"(vv.w) : "memory");
        }
        fence_async_smem();
        __syncwarp();
        if (lane == 0) {
          tma2d_store(&tmKVM, sb + OFF_EXP, hf * 64, (s * H_ + head) * 16);
          bulk_commit();
          if (last) {
            bulk_wait0();
            asm volatile("red.relaxed.gpu.global.add.u32 [%0],1;" ::"l"(&g_flags.mem[s]) : "memory");
          }
        }
        __syncwarp();
      } else if (pw == 1) {
        if (!last) {
          if (lane < 8) { mbar_wait(bar + (B_O + lane) * 8, par); mbar_expect(bar + (B_O + lane) * 8, 1024); }
          __syncwarp();
          if (lane == 0 && s + 2 < NSEG - 1) {
            if (((s + 2) & 3) == 0) { wait_flag(&g_flags.kv[(s + 2) >> 2], 64); fence_async_all(); }
            mbar_expect(bar + (B_TOK + par) * 8, 8192);
            tma2d(kxb, &tmKV, col0, (s + 2) * 32, bar + (B_TOK + par) * 8);
            tma2d(kxb + 4096, &tmKV, 4096 + col0, (s + 2) * 32, bar + (B_TOK + par) * 8);
          }
        }
      } else if (pw == 2) {
        if (lane == 0) {
          bulk_wait0();
          if (cl == (s & 7)) {
            const int base = (((s + 3) & 7) * 8 + rank) * 160;
            asm volatile("cp.async.bulk.global.shared::cta.bulk_group [%0],[%1],2560;" ::"l"(g_acc4 + base * 4), "r"(sb + OFF_ZERO) : "memory");
            asm volatile("cp.async.bulk.global.shared::cta.bulk_group [%0],[%1],1280;" ::"l"(g_acc2 + base * 2), "r"(sb + OFF_ZERO) : "memory");
            bulk_commit();
            if (last) bulk_wait0();
          }
        }
        __syncwarp();
      }
    }
  }
  asm volatile("barrier.cluster.arrive.release.aligned;" ::: "memory");
  asm volatile("barrier.cluster.wait.acquire.aligned;" ::: "memory");
}
}

namespace g1 {
#define G1_NST 3
constexpr int NST = G1_NST;
constexpr uint32_t STAGE = 49152;
constexpr uint32_t OFF_STG = NST * STAGE;
constexpr uint32_t STG_BYTES = NST == 3 ? 65536 : 32768;
constexpr uint32_t OFF_BAR = OFF_STG + STG_BYTES;
constexpr uint32_t SMEM_BYTES = OFF_BAR + 128 + 1024;
constexpr int NTILES = 16 * 32;

__device__ __forceinline__ void role(const CUtensorMap& tmX, const CUtensorMap& tmWk, const CUtensorMap& tmWv, const CUtensorMap& tmKVst,
                                     uint8_t* smem_raw, int cta, int ncta) {
  const uint32_t sb = (smem_u32(smem_raw) + 1023) & ~1023u;
  const int tid = threadIdx.x, lane = tid & 31;
  const int warp = __shfl_sync(0xffffffffu, tid >> 5, 0);
  const int wg = warp >> 2, w4 = warp & 3;
  const uint32_t full = sb + OFF_BAR, empty = full + NST * 8;
  if (tid == 0) {
    for (int i = 0; i < NST; i++) { mbar_init(full + i * 8, 1); mbar_init(empty + i * 8, 2); }
    asm volatile("fence.mbarrier_init.release.cluster;" ::: "memory");
    fence_async_smem();
  }
  __syncthreads();
  const int ntile = cta < NTILES ? (NTILES - cta + ncta - 1) / ncta : 0;
  const int total = ntile * 10;
  const bool t0 = tid == 0, lead = (tid & 127) == 0;
  auto issue = [&](int it) {
    const int t = cta + (it / 10) * ncta, kb = it % 10, m = t >> 5, n = t & 31, st = it % NST;
    const uint32_t a = sb + st * STAGE, fb = full + st * 8;
    expect_if(t0, fb, STAGE);
    tma2d_if(t0, a, &tmX, kb * 64, m * 128, fb);
    const CUtensorMap* tw = n < 16 ? &tmWk : &tmWv;
#pragma unroll
    for (int i = 0; i < 4; i++) tma2d_if(t0, a + 16384 + i * 8192, tw, (n & 15) * 256 + i * 64, kb * 64, fb);
  };
  for (int it = 0; it < NST && it < total; it++) issue(it);

  float acc[128];
  int it = 0, pending_m = -1;
  for (int ti = 0; ti < ntile; ti++) {
    const int t = cta + ti * ncta, m = t >> 5, n = t & 31;
#pragma unroll 1
    for (int kb = 0; kb < 10; kb++, it++) {
      const int st = it % NST;
      bwait(full + st * 8, (it / NST) & 1);
      const uint32_t a = sb + st * STAGE;
      const uint64_t da = desc_k(a + wg * 8192), db = desc_mn(a + 16384);
      wg_fence();
#pragma unroll
      for (int k = 0; k < 4; k++) wgmma_n256(acc, da + k * 2, db + k * 128, (kb | k) != 0);
      wg_commit();
      if (kb > 0) {
        wg_wait<1>();
        const int pst = (it - 1) % NST;
        arrive_if(lead, empty + pst * 8);
        if (it - 1 + NST < total) { bwait(empty + pst * 8, ((it - 1) / NST) & 1); issue(it - 1 + NST); }
      }
      if (kb == 3 && pending_m >= 0) publish_if(lead, &g_flags.kv[pending_m]);
    }
    wg_wait<0>();
    {
      const int pst = (it - 1) % NST;
      arrive_if(lead, empty + pst * 8);
      if (it - 1 + NST < total) { bwait(empty + pst * 8, ((it - 1) / NST) & 1); issue(it - 1 + NST); }
    }
    constexpr int NR = NST == 3 ? 1 : 2;
    constexpr int NB = 4 / NR;
    const uint32_t stg = sb + OFF_STG + wg * (STG_BYTES / 2);
    const int q4 = lane >> 3, rr = lane & 7;
    const int row = w4 * 16 + (q4 & 1) * 8 + rr;
#pragma unroll
    for (int r = 0; r < NR; r++) {
      if ((tid & 127) == 0) bulk_wait_read0();
      bar_sync(1 + wg, 128);
#pragma unroll
      for (int jj = 0; jj < 8 * NB; jj += 2) {
        const int j = r * 8 * NB + jj;
        const int ch = (jj + (q4 >> 1)) & 7;
        stsm4(stg + (jj >> 3) * 8192 + row * 128 + ((ch ^ rr) << 4),
              pack_bf16(acc[4 * j], acc[4 * j + 1]), pack_bf16(acc[4 * j + 2], acc[4 * j + 3]),
              pack_bf16(acc[4 * j + 4], acc[4 * j + 5]), pack_bf16(acc[4 * j + 6], acc[4 * j + 7]));
      }
      fence_async_smem();
      bar_sync(1 + wg, 128);
      if ((tid & 127) == 0) {
#pragma unroll
        for (int i = 0; i < NB; i++) tma2d_store(&tmKVst, stg + i * 8192, n * 256 + (r * NB + i) * 64, m * 128 + wg * 64);
        bulk_commit();
      }
    }
    pending_m = m;
  }
  if (pending_m >= 0) publish_if(lead, &g_flags.kv[pending_m]);
}
}

struct K1Maps { CUtensorMap wq80, wk80, wv80, wo, wo4, kv32, kvm, x, wk64, wv64, kvst; };
constexpr uint32_t K1_SMEM = chain::SMEM_BYTES > g1::SMEM_BYTES ? chain::SMEM_BYTES : g1::SMEM_BYTES;

__global__ void __cluster_dims__(8, 1, 1) __launch_bounds__(256, 1)
k1_kernel(const __grid_constant__ K1Maps mp, const bf16* __restrict__ mem0
          ) {
  extern __shared__ uint8_t smem_raw[];
  asm volatile("griddepcontrol.launch_dependents;");
  if (blockIdx.x < 64) chain::chain_role(mp.wq80, mp.wk80, mp.wv80, mp.wo, mp.wo4, mp.kv32, mp.kvm, mem0, smem_raw);
  else g1::role(mp.x, mp.wk64, mp.wv64, mp.kvst, smem_raw, blockIdx.x - 64, gridDim.x - 64);
}

namespace k2 {
constexpr int NST = 3;
constexpr uint32_t STAGE = 32768;
constexpr uint32_t OFF_BAR = 110592;
constexpr uint32_t SMEM_BYTES = OFF_BAR + 128 + 1024;
constexpr int B_FULL = 0, B_EMPTY = 3, B_KV = 6, B_KM = 7;
constexpr int NG4 = 80;
constexpr int SPLIT_FROM = 14;
constexpr int NSPLIT = 8;
constexpr __host__ __device__ int items_of(int m) { return 32 + (m >= SPLIT_FROM ? 5 * NSPLIT : 5); }
constexpr __host__ __device__ int total_items() { int t = NG4; for (int m = 0; m < 16; m++) t += items_of(m); return t; }
struct Maps { CUtensorMap x, wq, kv128, kvm, ost, o, wo, out; };

__device__ __forceinline__ void gemm128(float (&acc)[64], const CUtensorMap* ta, int a_c0, int a_row, const CUtensorMap* tb, int b_col, int b_row0,
                                        int nkb, uint32_t sb, int tid, int wg) {
  const uint32_t full = sb + OFF_BAR + B_FULL * 8, empty = sb + OFF_BAR + B_EMPTY * 8;
  const bool t0 = tid == 0, lead = (tid & 127) == 0;
  auto issue = [&](int it) {
    const int st = it % NST;
    const uint32_t a = sb + st * STAGE, fb = full + st * 8;
    expect_if(t0, fb, STAGE);
    tma2d_if(t0, a, ta, a_c0 + it * 64, a_row, fb);
    tma2d_if(t0, a + 16384, tb, b_col, b_row0 + it * 64, fb);
    tma2d_if(t0, a + 24576, tb, b_col + 64, b_row0 + it * 64, fb);
  };
  for (int it = 0; it < NST && it < nkb; it++) issue(it);
#pragma unroll 1
  for (int it = 0; it < nkb; it++) {
    const int st = it % NST;
    bwait(full + st * 8, (it / NST) & 1);
    const uint32_t a = sb + st * STAGE;
    const uint64_t da = desc_k(a + wg * 8192), db = desc_mn(a + 16384);
    wg_fence();
#pragma unroll
    for (int k = 0; k < 4; k++) wgmma_n128(acc, da + k * 2, db + k * 128, (it | k) != 0);
    wg_commit();
    if (it > 0) {
      wg_wait<1>();
      const int pst = (it - 1) % NST;
      arrive_if(lead, empty + pst * 8);
      if (it - 1 + NST < nkb) { bwait(empty + pst * 8, ((it - 1) / NST) & 1); issue(it - 1 + NST); }
    }
  }
  wg_wait<0>();
}

__device__ __forceinline__ void stage_tile(const float (&c)[64], uint32_t stg, int row0, int lane) {
  const int q4 = lane >> 3, rr = lane & 7;
  const int row = row0 + (q4 & 1) * 8 + rr;
#pragma unroll
  for (int j = 0; j < 16; j += 2) {
    const int ch = (j + (q4 >> 1)) & 7;
    stsm4(stg + (j >> 3) * 16384 + row * 128 + ((ch ^ rr) << 4),
          pack_bf16(c[4 * j], c[4 * j + 1]), pack_bf16(c[4 * j + 2], c[4 * j + 3]),
          pack_bf16(c[4 * j + 4], c[4 * j + 5]), pack_bf16(c[4 * j + 6], c[4 * j + 7]));
  }
}

__device__ __forceinline__ void g2_item(const Maps& mp, int m, int h, uint32_t sb, int tid) {
  const int lane = tid & 31, warp = __shfl_sync(0xffffffffu, tid >> 5, 0), wg = warp >> 2, w4 = warp & 3;
  float acc[64];
  gemm128(acc, &mp.x, 0, m * 128, &mp.wq, h * 128, 0, 10, sb, tid, wg);
  uint32_t qa[8][4];
#pragma unroll
  for (int k = 0; k < 8; k++) {
    qa[k][0] = pack_bf16(acc[8 * k], acc[8 * k + 1]); qa[k][1] = pack_bf16(acc[8 * k + 2], acc[8 * k + 3]);
    qa[k][2] = pack_bf16(acc[8 * k + 4], acc[8 * k + 5]); qa[k][3] = pack_bf16(acc[8 * k + 6], acc[8 * k + 7]);
  }
  __syncthreads();
  const uint32_t bkv = sb + OFF_BAR + B_KV * 8, bkm = sb + OFF_BAR + B_KM * 8;
  const uint32_t sK = sb, sV = sb + STAGE, sM = sb + 2 * STAGE;
  if (tid == 0) {
    wait_flag(&g_flags.kv[m], 64);
    fence_async_all();
    mbar_expect(bkv, 65536);
    tma2d(sK, &mp.kv128, h * 128, m * 128, bkv);
    tma2d(sK + 16384, &mp.kv128, h * 128 + 64, m * 128, bkv);
    tma2d(sV, &mp.kv128, 4096 + h * 128, m * 128, bkv);
    tma2d(sV + 16384, &mp.kv128, 4096 + h * 128 + 64, m * 128, bkv);
    for (int i = 0; i < 4; i++) wait_flag(&g_flags.mem[4 * m + i], 64);
    fence_async_all();
    mbar_expect(bkm, 16384);
    for (int i = 0; i < 4; i++) {
      tma2d(sM + i * 4096, &mp.kvm, 0, ((4 * m + i) * H_ + h) * 16, bkm);
      tma2d(sM + i * 4096 + 2048, &mp.kvm, 64, ((4 * m + i) * H_ + h) * 16, bkm);
    }
  }
  __syncwarp();
  const int seg = 2 * wg + (w4 >> 1), hi = w4 & 1;
  const int q4 = lane >> 3, rr = lane & 7, g = lane >> 2, t = lane & 3;
  float sc[5][4];
#pragma unroll
  for (int n = 0; n < 5; n++) sc[n][0] = sc[n][1] = sc[n][2] = sc[n][3] = 0.f;
  mbar_wait(bkv, 0);
#pragma unroll
  for (int n = 0; n < 4; n++) {
    if (n < 2 || hi) {
      const uint32_t kr = sK + (seg * 32 + n * 8 + rr) * 128;
#pragma unroll
      for (int k2 = 0; k2 < 4; k2++) {
        uint32_t b[4];
        ldsm4(b, kr + (k2 >> 1) * 16384 + ((((k2 & 1) * 4 + q4) ^ rr) << 4));
        mma16816(sc[n + 1], qa[2 * k2], b[0], b[1]);
        mma16816(sc[n + 1], qa[2 * k2 + 1], b[2], b[3]);
      }
    }
  }
  mbar_wait(bkm, 0);
  {
    const uint32_t kr = sM + seg * 4096 + rr * 128;
#pragma unroll
    for (int k2 = 0; k2 < 4; k2++) {
      uint32_t b[4];
      ldsm4(b, kr + (k2 >> 1) * 2048 + ((((k2 & 1) * 4 + q4) ^ rr) << 4));
      mma16816(sc[0], qa[2 * k2], b[0], b[1]);
      mma16816(sc[0], qa[2 * k2 + 1], b[2], b[3]);
    }
  }
  __syncthreads();
  const int r0 = hi * 16 + g, r1 = r0 + 8;
  const float NEG = -1e30f;
#pragma unroll
  for (int n = 0; n < 4; n++) {
    const int k0 = n * 8 + 2 * t;
    if (k0 > r0) sc[n + 1][0] = NEG;
    if (k0 + 1 > r0) sc[n + 1][1] = NEG;
    if (k0 > r1) sc[n + 1][2] = NEG;
    if (k0 + 1 > r1) sc[n + 1][3] = NEG;
  }
  float m0 = NEG, m1 = NEG;
#pragma unroll
  for (int n = 0; n < 5; n++) { m0 = fmaxf(m0, fmaxf(sc[n][0], sc[n][1])); m1 = fmaxf(m1, fmaxf(sc[n][2], sc[n][3])); }
  m0 = fmaxf(m0, __shfl_xor_sync(0xffffffffu, m0, 1)); m1 = fmaxf(m1, __shfl_xor_sync(0xffffffffu, m1, 1));
  m0 = fmaxf(m0, __shfl_xor_sync(0xffffffffu, m0, 2)); m1 = fmaxf(m1, __shfl_xor_sync(0xffffffffu, m1, 2));
  const float sl2 = 0.08838834764831845f * 1.4426950408889634f;
  const float o0 = -m0 * sl2, o1 = -m1 * sl2;
  float s0 = 0.f, s1 = 0.f;
  uint32_t p[5][2];
#pragma unroll
  for (int n = 0; n < 5; n++) {
    const float e0 = ex2(fmaf(sc[n][0], sl2, o0)), e1 = ex2(fmaf(sc[n][1], sl2, o0));
    const float e2 = ex2(fmaf(sc[n][2], sl2, o1)), e3 = ex2(fmaf(sc[n][3], sl2, o1));
    s0 += e0 + e1; s1 += e2 + e3;
    p[n][0] = pack_bf16(e0, e1); p[n][1] = pack_bf16(e2, e3);
  }
  s0 += __shfl_xor_sync(0xffffffffu, s0, 1); s1 += __shfl_xor_sync(0xffffffffu, s1, 1);
  s0 += __shfl_xor_sync(0xffffffffu, s0, 2); s1 += __shfl_xor_sync(0xffffffffu, s1, 2);
  const float i0 = 1.0f / s0, i1 = 1.0f / s1;
  const uint32_t vrow = q4 == 0 ? sM + seg * 4096 + (8 + rr) * 128 : sV + (seg * 32 + (q4 - 1) * 8 + rr) * 128;
  const uint32_t vhalf = q4 == 0 ? 2048 : 16384;
  const uint32_t vlast = sV + (seg * 32 + 24 + rr) * 128;
  const uint32_t a0[4] = {p[0][0], p[0][1], p[1][0], p[1][1]}, a1[4] = {p[2][0], p[2][1], p[3][0], p[3][1]};
#pragma unroll
  for (int c4 = 0; c4 < 4; c4++) {
    uint32_t bl[4];
    if (hi) ldsm4t(bl, vlast + (c4 >> 1) * 16384 + ((((c4 & 1) * 4 + q4) ^ rr) << 4));
#pragma unroll
    for (int i = 0; i < 4; i++) {
      const int c = c4 * 4 + i;
      uint32_t b[4];
      ldsm4t(b, vrow + (c >> 3) * vhalf + (((c & 7) ^ rr) << 4));
      float o[4] = {0.f, 0.f, 0.f, 0.f};
      mma16816(o, a0, b[0], b[1]);
      mma16816(o, a1, b[2], b[3]);
      if (hi) {
        asm volatile("mma.sync.aligned.m16n8k8.row.col.f32.bf16.bf16.f32 {%0,%1,%2,%3},{%4,%5},{%6},{%0,%1,%2,%3};"
                     : "+f"(o[0]), "+f"(o[1]), "+f"(o[2]), "+f"(o[3]) : "r"(p[4][0]), "r"(p[4][1]), "r"(bl[i]));
      }
      acc[4 * c] = o[0] * i0; acc[4 * c + 1] = o[1] * i0; acc[4 * c + 2] = o[2] * i1; acc[4 * c + 3] = o[3] * i1;
    }
  }
  stage_tile(acc, sK, wg * 64 + w4 * 16, lane);
  fence_async_smem();
  __syncthreads();
  if (tid == 0) {
    tma2d_store(&mp.ost, sK, h * 128, m * 128);
    tma2d_store(&mp.ost, sK + 16384, h * 128 + 64, m * 128);
    bulk_commit();
    bulk_wait0();
    fence_async_all();
    red_release(&g_flags.o[m], 1u);
  }
}

__device__ __forceinline__ void g3_item(const Maps& mp, int m, int n, int ks, int nsplit, bf16* __restrict__ out, uint32_t sb, int tid, volatile int* s_flag) {
  const int lane = tid & 31, warp = __shfl_sync(0xffffffffu, tid >> 5, 0), wg = warp >> 2, w4 = warp & 3;
  if (tid == 0) { wait_flag(&g_flags.o[m], 32); fence_async_all(); }
  __syncthreads();
  float acc[64];
  const int nkb = 64 / nsplit;
  gemm128(acc, &mp.o, ks * nkb * 64, m * 128, &mp.wo, n * 128, ks * nkb * 64, nkb, sb, tid, wg);
  if (nsplit > 1) {
    float* part = g_part + (size_t)(((m - SPLIT_FROM) * 5 + n) * NSPLIT) * 16384;
    float4* mine = reinterpret_cast<float4*>(part + (size_t)ks * 16384) + tid;
#pragma unroll
    for (int i = 0; i < 16; i++) __stcg(mine + i * 256, make_float4(acc[4 * i], acc[4 * i + 1], acc[4 * i + 2], acc[4 * i + 3]));
    __threadfence();
    __syncthreads();
    if (tid == 0) *s_flag = (int)atomicAdd(&g_flags.part[(m - SPLIT_FROM) * 5 + n], 1u);
    __syncthreads();
    if (*s_flag != nsplit - 1) return;
    __threadfence();
#pragma unroll
    for (int i = 0; i < 64; i++) acc[i] = 0.f;
    for (int k = 0; k < nsplit; k++) {
      const float4* src = reinterpret_cast<const float4*>(part + (size_t)k * 16384) + tid;
#pragma unroll
      for (int i = 0; i < 16; i++) {
        const float4 v = __ldcg(src + i * 256);
        acc[4 * i] += v.x; acc[4 * i + 1] += v.y; acc[4 * i + 2] += v.z; acc[4 * i + 3] += v.w;
      }
    }
  }
  __syncthreads();
  stage_tile(acc, sb, wg * 64 + w4 * 16, lane);
  fence_async_smem();
  __syncthreads();
  if (tid == 0) {
    tma2d_store(&mp.out, sb, n * 128, m * 128);
    tma2d_store(&mp.out, sb + 16384, n * 128 + 64, m * 128);
    bulk_commit();
    bulk_wait0();
  }
}
}

namespace conv {
constexpr uint32_t U_CH = 5120;
constexpr uint32_t OFF_R = 8 * U_CH;
constexpr uint32_t R1_OFF = 4288, R_CH = R1_OFF + 4224;
static_assert(OFF_R + 8 * R_CH <= k2::OFF_BAR, "conv smem");

__device__ __forceinline__ uint32_t lds32(uint32_t a) { uint32_t v; asm volatile("ld.shared.u32 %0,[%1];" : "=r"(v) : "r"(a) : "memory"); return v; }
__device__ __forceinline__ void sts128u(uint32_t a, uint32_t x, uint32_t y, uint32_t z, uint32_t w) {
  asm volatile("st.shared.v4.u32 [%0],{%1,%2,%3,%4};" ::"r"(a), "r"(x), "r"(y), "r"(z), "r"(w) : "memory");
}
__device__ __forceinline__ __nv_bfloat162 as_bf2(uint32_t v) { return *reinterpret_cast<__nv_bfloat162*>(&v); }
__device__ __forceinline__ uint32_t as_u32(__nv_bfloat162 v) { return *reinterpret_cast<uint32_t*>(&v); }

template <int NU0>
__device__ __forceinline__ void phase(float (&acc)[4][4][4], uint32_t (&V)[16], uint32_t vadr, uint32_t ub, int q4, int rr) {
  constexpr int X0 = -3 + 32 * NU0;
#pragma unroll 1
  for (int it = 0; it < 4; it++) {
    const int xb = X0 + 8 * it;
#pragma unroll
    for (int u = 0; u < 8; u++) {
      const int x = xb + u;
      constexpr int RB = 2 * (-3) + 16 * 4;
      V[(RB + 2 * u + 6) & 15] = lds32(vadr - 16 * (2 * x + 6));
      V[(RB + 2 * u + 7) & 15] = lds32(vadr - 16 * (2 * x + 7));
      const int r = (1 + u) & 3;
      const int sh = (x + 3) >> 2;
      const int ch0 = r == 0 ? 0 : (8 - 2 * r);
      uint32_t b[2][4];
      const int rowx = (rr - sh) & 7;
      const uint32_t u2 = ub + (rr + 8 - sh) * 128 + (((ch0 + (q4 & 1)) ^ rowx) << 4);
      const uint32_t u4 = u2 + (q4 >> 1) * 1024;
      if (NU0 == 0) ldsm4(b[0], u4);
      if (NU0 == 1) ldsm2(b[0][2], b[0][3], u2 + 1024);
      if (NU0 <= 2) ldsm4(b[1], u4 + 2048);
      if (NU0 == 3) ldsm2(b[1][2], b[1][3], u2 + 3072);
#pragma unroll
      for (int mu = 0; mu < 4; mu++) {
        const uint32_t a[4] = {V[(RB + 2 * (u + mu)) & 15], V[(RB + 2 * (u + mu) + 1) & 15], V[(RB + 2 * (u + mu) - 1) & 15], V[(RB + 2 * (u + mu)) & 15]};
#pragma unroll
        for (int nu = NU0; nu < 4; nu++) mma16816(acc[mu][nu], a, b[nu >> 1][(nu & 1) * 2], b[nu >> 1][(nu & 1) * 2 + 1]);
      }
    }
  }
}

__device__ __forceinline__ void item(int d0, const bf16* __restrict__ q, const bf16* __restrict__ k, const bf16* __restrict__ v,
                                     const bf16* __restrict__ shift_k, const bf16* __restrict__ ssm_k, const bf16* __restrict__ ssm_D,
                                     bf16* __restrict__ out, uint32_t sb, int tid) {
  const int lane = tid & 31, warp = tid >> 5;
  const uint32_t r0 = sb + OFF_R + warp * R_CH, r1 = r0 + R1_OFF;
  {
    const uint4* src = reinterpret_cast<const uint4*>(ssm_k + (size_t)(d0 + warp) * S_);
#pragma unroll
    for (int j = 0; j < 8; j++) {
      const int c = lane + 32 * j;
      const uint4 e = __ldg(src + c);
      sts128u(r1 + (1020 - 4 * c) * 4, __byte_perm(e.w, 0, 0x1032), __byte_perm(e.z, 0, 0x1032), __byte_perm(e.y, 0, 0x1032), __byte_perm(e.x, 0, 0x1032));
    }
    if (lane < 8) sts128u(r1 + (1024 + 4 * lane) * 4, 0, 0, 0, 0);
  }
  {
    const int ch = tid >> 5;
    sts128u(sb + ch * U_CH + lane * 32, 0, 0, 0, 0);
    sts128u(sb + ch * U_CH + lane * 32 + 16, 0, 0, 0, 0);
  }
  {
    uint32_t sw[4][4];
#pragma unroll
    for (int c = 0; c < 4; c++) {
      const uint2 w0 = __ldg(reinterpret_cast<const uint2*>(shift_k + (d0 + 2 * c) * 4)), w1 = __ldg(reinterpret_cast<const uint2*>(shift_k + (d0 + 2 * c + 1) * 4));
      sw[0][c] = __byte_perm(w0.x, w1.x, 0x5410); sw[1][c] = __byte_perm(w0.x, w1.x, 0x7632);
      sw[2][c] = __byte_perm(w0.y, w1.y, 0x5410); sw[3][c] = __byte_perm(w0.y, w1.y, 0x7632);
    }
    const int t0 = 8 * tid;
    uint32_t kvw[8][4];
    uint4 kw[3];
#pragma unroll
    for (int j = 0; j < 3; j++) kw[j] = t0 > 0 ? __ldg(reinterpret_cast<const uint4*>(k + (size_t)(t0 - 3 + j) * D_ + d0)) : make_uint4(0, 0, 0, 0);
#pragma unroll
    for (int j = 0; j < 8; j++) {
      const uint4 kc = __ldg(reinterpret_cast<const uint4*>(k + (size_t)(t0 + j) * D_ + d0));
      const uint4 vc = __ldg(reinterpret_cast<const uint4*>(v + (size_t)(t0 + j) * D_ + d0));
      const uint32_t x0[4] = {kw[0].x, kw[0].y, kw[0].z, kw[0].w}, x1[4] = {kw[1].x, kw[1].y, kw[1].z, kw[1].w};
      const uint32_t x2[4] = {kw[2].x, kw[2].y, kw[2].z, kw[2].w}, x3[4] = {kc.x, kc.y, kc.z, kc.w}, vv[4] = {vc.x, vc.y, vc.z, vc.w};
#pragma unroll
      for (int c = 0; c < 4; c++) {
        __nv_bfloat162 a = __hmul2_rn(as_bf2(x0[c]), as_bf2(sw[3][c]));
        a = __hadd2_rn(a, __hmul2_rn(as_bf2(x1[c]), as_bf2(sw[2][c])));
        a = __hadd2_rn(a, __hmul2_rn(as_bf2(x2[c]), as_bf2(sw[1][c])));
        a = __hadd2_rn(a, __hmul2_rn(as_bf2(x3[c]), as_bf2(sw[0][c])));
        kvw[j][c] = as_u32(__hmul2_rn(a, as_bf2(vv[c])));
      }
      kw[0] = kw[1]; kw[1] = kw[2]; kw[2] = kc;
    }
    const int ri = (tid >> 3) + 8;
    const uint32_t ua = sb + ri * 128 + (((tid & 7) ^ (ri & 7)) << 4);
#pragma unroll
    for (int c = 0; c < 4; c++) {
      sts128u(ua + (2 * c) * U_CH, __byte_perm(kvw[0][c], kvw[1][c], 0x5410), __byte_perm(kvw[2][c], kvw[3][c], 0x5410),
              __byte_perm(kvw[4][c], kvw[5][c], 0x5410), __byte_perm(kvw[6][c], kvw[7][c], 0x5410));
      sts128u(ua + (2 * c + 1) * U_CH, __byte_perm(kvw[0][c], kvw[1][c], 0x7632), __byte_perm(kvw[2][c], kvw[3][c], 0x7632),
              __byte_perm(kvw[4][c], kvw[5][c], 0x7632), __byte_perm(kvw[6][c], kvw[7][c], 0x7632));
    }
  }
  __syncwarp();
  for (int i = lane; i < 1056; i += 32) {
    const uint32_t lo = i > 0 ? lds32(r1 + (i - 1) * 4) : 0u, hi = lds32(r1 + i * 4);
    const uint32_t w = __byte_perm(lo, hi, 0x5432);
    asm volatile("st.shared.u32 [%0],%1;" ::"r"(r0 + i * 4), "r"(w) : "memory");
  }
  __syncthreads();

  const int g = lane >> 2, t = lane & 3, q4 = lane >> 3, rr = lane & 7;
  float acc[4][4][4];
#pragma unroll
  for (int a = 0; a < 4; a++)
#pragma unroll
    for (int b = 0; b < 4; b++) acc[a][b][0] = acc[a][b][1] = acc[a][b][2] = acc[a][b][3] = 0.f;
  const uint32_t vadr = ((g & 1) ? r1 : r0) + ((2048 - g + 2 * t) >> 1) * 4;
  uint32_t V[16];
  {
    constexpr int RB = 2 * (-3) + 16 * 4;
#pragma unroll
    for (int n = -7; n < 0; n++) V[(RB + n + 6) & 15] = lds32(vadr - 16 * n);
  }
  const uint32_t ub = sb + warp * U_CH;
  phase<0>(acc, V, vadr, ub, q4, rr);
  phase<1>(acc, V, vadr, ub, q4, rr);
  phase<2>(acc, V, vadr, ub, q4, rr);
  phase<3>(acc, V, vadr, ub, q4, rr);
  __syncthreads();

  const float Dv = __bfloat162float(ssm_D[d0 + warp]);
  const uint32_t stg = sb + OFF_R;
#pragma unroll
  for (int mu = 0; mu < 4; mu++)
#pragma unroll
    for (int nu = 0; nu < 4; nu++)
#pragma unroll
      for (int e = 0; e < 4; e++) {
        const int a = 16 * mu + g + (e >> 1) * 8, i = 8 * nu + 2 * t + (e & 1);
        const int ri = i + 8;
        unsigned short raw;
        asm volatile("ld.shared.u16 %0,[%1];" : "=h"(raw) : "r"(ub + ri * 128 + (((a >> 3) ^ (ri & 7)) << 4) + (a & 7) * 2) : "memory");
        const float kv = __uint_as_float((uint32_t)raw << 16);
        const float y = __bfloat162float(__float2bfloat16(acc[mu][nu][e]));
        const float w = __bfloat162float(__float2bfloat16(kv * Dv));
        const bf16 z = __float2bfloat16(y + w);
        asm volatile("st.shared.u16 [%0],%1;" ::"r"(stg + (64 * i + a) * 16 + warp * 2), "h"(*reinterpret_cast<const unsigned short*>(&z)) : "memory");
      }
  __syncthreads();
#pragma unroll
  for (int j = 0; j < 8; j++) {
    const int tt = tid + 256 * j;
    const uint4 yv = lds128u(stg + tt * 16);
    const uint4 qv = __ldg(reinterpret_cast<const uint4*>(q + (size_t)tt * D_ + d0));
    uint4 o;
    o.x = as_u32(__hmul2_rn(as_bf2(qv.x), as_bf2(yv.x))); o.y = as_u32(__hmul2_rn(as_bf2(qv.y), as_bf2(yv.y)));
    o.z = as_u32(__hmul2_rn(as_bf2(qv.z), as_bf2(yv.z))); o.w = as_u32(__hmul2_rn(as_bf2(qv.w), as_bf2(yv.w)));
    *reinterpret_cast<uint4*>(out + (size_t)tt * 1280 + 640 + d0) = o;
  }
}
}

struct ConvArgs { const bf16 *q, *k, *v, *shift_k, *ssm_k, *ssm_D; bf16* out; };

__global__ void __launch_bounds__(256, 2) k2_kernel(const __grid_constant__ k2::Maps mp, const ConvArgs ca) {
  extern __shared__ uint8_t smem_raw[];
  __shared__ int s_item;
  const uint32_t sb = (smem_u32(smem_raw) + 1023) & ~1023u;
  const int tid = threadIdx.x;
  if (tid == 0) {
    s_item = (int)atomicAdd(&g_flags.ticket, 1u);
    const uint32_t bar = sb + k2::OFF_BAR;
    for (int i = 0; i < 3; i++) { mbar_init(bar + (k2::B_FULL + i) * 8, 1); mbar_init(bar + (k2::B_EMPTY + i) * 8, 2); }
    mbar_init(bar + k2::B_KV * 8, 1); mbar_init(bar + k2::B_KM * 8, 1);
    asm volatile("fence.mbarrier_init.release.cluster;" ::: "memory");
    fence_async_smem();
  }
  __syncthreads();
  int item = s_item;
  __syncthreads();
  if (item < k2::NG4) {
    conv::item(item * 8, ca.q, ca.k, ca.v, ca.shift_k, ca.ssm_k, ca.ssm_D, ca.out, sb, tid);
  } else {
    item -= k2::NG4;
    int m = 0;
    while (item >= k2::items_of(m)) { item -= k2::items_of(m); m++; }
    if (item < 32) k2::g2_item(mp, m, item, sb, tid);
    else {
      item -= 32;
      if (m >= k2::SPLIT_FROM) k2::g3_item(mp, m, item / k2::NSPLIT, item % k2::NSPLIT, k2::NSPLIT, ca.out, sb, tid, &s_item);
      else k2::g3_item(mp, m, item, 0, 1, ca.out, sb, tid, &s_item);
    }
  }
  __syncthreads();
  if (tid == 0) {
    __threadfence();
    if (atomicAdd(&g_flags.done, 1u) == gridDim.x - 1) {
      unsigned* p = reinterpret_cast<unsigned*>(&g_flags);
      for (int i = 0; i < (int)(sizeof(Flags) / 4); i++) p[i] = 0;
      __threadfence();
    }
  }
}

typedef CUresult (*EncodeFn)(CUtensorMap*, CUtensorMapDataType, cuuint32_t, void*, const cuuint64_t*, const cuuint64_t*, const cuuint32_t*,
                             const cuuint32_t*, CUtensorMapInterleave, CUtensorMapSwizzle, CUtensorMapL2promotion, CUtensorMapFloatOOBfill);
static EncodeFn get_encode() {
  static EncodeFn fn = nullptr;
  if (!fn) {
    void* p = nullptr; cudaDriverEntryPointQueryResult st;
    cudaGetDriverEntryPoint("cuTensorMapEncodeTiled", &p, cudaEnableDefault, &st);
    fn = (EncodeFn)p;
  }
  return fn;
}
static CUtensorMap make_map2d(const void* base, uint64_t cols, uint64_t rows, uint64_t pitch_elems, uint32_t box_c, uint32_t box_r,
                              CUtensorMapSwizzle sw = CU_TENSOR_MAP_SWIZZLE_128B) {
  CUtensorMap m;
  cuuint64_t dims[2] = {cols, rows};
  cuuint64_t strides[1] = {pitch_elems * 2};
  cuuint32_t box[2] = {box_c, box_r};
  cuuint32_t es[2] = {1, 1};
  CUresult r = get_encode()(&m, CU_TENSOR_MAP_DATA_TYPE_BFLOAT16, 2, (void*)base, dims, strides, box, es, CU_TENSOR_MAP_INTERLEAVE_NONE, sw,
                            CU_TENSOR_MAP_L2_PROMOTION_L2_128B, CU_TENSOR_MAP_FLOAT_OOB_FILL_NONE);
  if (r != CUDA_SUCCESS) fprintf(stderr, "tensor map encode failed %d\n", (int)r);
  return m;
}

struct HostState {
  bool init;
  void* key[13];
  void* out;
  K1Maps k1;
  k2::Maps k2;
  int k1_clusters;
};
static HostState hs;

static void host_setup(void* const* d_in, void* d_out) {
  bool same = hs.init && hs.out == d_out;
  for (int i = 0; same && i < 13; i++) same = hs.key[i] == d_in[i];
  if (same) return;
  for (int i = 0; i < 13; i++) hs.key[i] = d_in[i];
  hs.out = d_out;
  void* kv; cudaGetSymbolAddress(&kv, g_KV);
  hs.k1.wq80 = make_map2d(d_in[2], 4096, 640, 4096, 64, 80);
  hs.k1.wk80 = make_map2d(d_in[3], 4096, 640, 4096, 64, 80);
  hs.k1.wv80 = make_map2d(d_in[4], 4096, 640, 4096, 64, 80);
  hs.k1.wo = make_map2d(d_in[5], 640, 4096, 640, 64, 64);
  hs.k1.wo4 = make_map2d(d_in[5], 640, 4096, 640, 16, 64, CU_TENSOR_MAP_SWIZZLE_32B);
  hs.k1.kv32 = make_map2d(kv, 8192, 2048, 8192, 64, 32);
  void* kvm; cudaGetSymbolAddress(&kvm, g_KVM);
  hs.k1.kvm = make_map2d(kvm, 128, 64 * 32 * 16, 128, 64, 16);
  hs.k1.x = make_map2d(d_in[0], 640, 2048, 640, 64, 128);
  hs.k1.wk64 = make_map2d(d_in[3], 4096, 640, 4096, 64, 64);
  hs.k1.wv64 = make_map2d(d_in[4], 4096, 640, 4096, 64, 64);
  hs.k1.kvst = make_map2d(kv, 8192, 2048, 8192, 64, 64);
  void* o; cudaGetSymbolAddress(&o, g_O);
  hs.k2.x = hs.k1.x;
  hs.k2.wq = make_map2d(d_in[2], 4096, 640, 4096, 64, 64);
  hs.k2.kv128 = make_map2d(kv, 8192, 2048, 8192, 64, 128);
  hs.k2.kvm = hs.k1.kvm;
  hs.k2.ost = make_map2d(o, 4096, 2048, 4096, 64, 128);
  hs.k2.o = hs.k2.ost;
  hs.k2.wo = hs.k1.wo;
  hs.k2.out = make_map2d(d_out, 1280, 2048, 1280, 64, 128);
  if (!hs.init) {
    cudaFuncSetAttribute(k2_kernel, cudaFuncAttributeMaxDynamicSharedMemorySize, k2::SMEM_BYTES);
    cudaFuncSetAttribute(k1_kernel, cudaFuncAttributeMaxDynamicSharedMemorySize, K1_SMEM);
    cudaLaunchConfig_t cfg = {};
    cfg.gridDim = dim3(128); cfg.blockDim = dim3(256); cfg.dynamicSmemBytes = K1_SMEM;
    cudaLaunchAttribute at[1];
    at[0].id = cudaLaunchAttributeClusterDimension; at[0].val.clusterDim.x = 8; at[0].val.clusterDim.y = 1; at[0].val.clusterDim.z = 1;
    cfg.attrs = at; cfg.numAttrs = 1;
    int n = 0;
    cudaOccupancyMaxActiveClusters(&n, k1_kernel, &cfg);
    if (n < 9) n = 9;
    if (n > 16) n = 16;
    hs.k1_clusters = n;
  }
  hs.init = true;
}
static void launch_k1(void* const* d_in, cudaStream_t st) {
  k1_kernel<<<hs.k1_clusters * 8, 256, K1_SMEM, st>>>(hs.k1, (const bf16*)d_in[1]);
}

static void launch_k2(void* const* d_in, void* d_out, cudaStream_t st) {
  ConvArgs ca;
  ca.q = (const bf16*)d_in[7]; ca.k = (const bf16*)d_in[8]; ca.v = (const bf16*)d_in[9];
  ca.shift_k = (const bf16*)d_in[10]; ca.ssm_k = (const bf16*)d_in[11]; ca.ssm_D = (const bf16*)d_in[12]; ca.out = (bf16*)d_out;
  cudaLaunchConfig_t cfg = {};
  cfg.gridDim = dim3(k2::total_items()); cfg.blockDim = dim3(256); cfg.dynamicSmemBytes = k2::SMEM_BYTES; cfg.stream = st;
  cudaLaunchAttribute at[1];
  at[0].id = cudaLaunchAttributeProgrammaticStreamSerialization; at[0].val.programmaticStreamSerializationAllowed = 1;
  cfg.attrs = at; cfg.numAttrs = 1;
  cudaLaunchKernelEx(&cfg, k2_kernel, hs.k2, ca);
}

extern "C" void kernel_launch(void* const* d_in, const int* in_sizes, int n_in, void* d_out, int out_size) {
  cudaStream_t st = cudaStreamPerThread;
  host_setup(d_in, d_out);
  launch_k1(d_in, st);
  launch_k2(d_in, d_out, st);
}
```

```cpp
#include <cuda_runtime.h>
#include <cuda_bf16.h>
#include <cuda.h>
#include <stdint.h>
#include <stdio.h>
#include <math.h>

typedef __nv_bfloat16 bf16;

constexpr int S_ = 2048, D_ = 640, H_ = 32, DH_ = 128, HD_ = 4096, NSEG = 64, M_ = 8;

__device__ __align__(1024) bf16 g_KV[(size_t)S_ * 8192];
__device__ __align__(1024) bf16 g_KVM[(size_t)NSEG * H_ * 2 * M_ * DH_];
__device__ __align__(1024) bf16 g_O[(size_t)S_ * HD_];
__device__ __align__(1024) bf16 g_uT[(size_t)D_ * S_];
__device__ __align__(1024) float g_acc4[8 * 8 * 160 * 4];
__device__ __align__(1024) float g_acc2[8 * 8 * 160 * 2];
__device__ __align__(1024) float g_part[6 * 5 * 16 * 128 * 128];
struct Flags {
  unsigned kv[16];
  unsigned mem[64];
  unsigned o[16];
  unsigned oh[4];
  unsigned part[40];
  unsigned cva[16];
  unsigned cvb[16];
  unsigned ticket;
};
__device__ Flags g_flags2[2];
__device__ unsigned g_epoch;
__device__ unsigned g_cur;
__shared__ int s_par;
#define g_flags g_flags2[s_par]

__device__ __forceinline__ uint32_t smem_u32(const void* p) { return (uint32_t)__cvta_generic_to_shared(p); }
__device__ __forceinline__ uint32_t mapa(uint32_t a, uint32_t r) {
  uint32_t o; asm("mapa.shared::cluster.u32 %0,%1,%2;" : "=r"(o) : "r"(a), "r"(r)); return o;
}
__device__ __forceinline__ void mbar_init(uint32_t a, uint32_t c) { asm volatile("mbarrier.init.shared::cta.b64 [%0],%1;" ::"r"(a), "r"(c) : "memory"); }
__device__ __forceinline__ void mbar_expect(uint32_t a, uint32_t tx) { asm volatile("mbarrier.arrive.expect_tx.shared::cta.b64 _,[%0],%1;" ::"r"(a), "r"(tx) : "memory"); }
__device__ __forceinline__ bool mbar_try(uint32_t a, uint32_t ph) {
  uint32_t ok;
  asm volatile("{\n.reg .pred p;\nmbarrier.try_wait.parity.shared::cta.b64 p,[%1],%2;\nselp.u32 %0,1,0,p;\n}" : "=r"(ok) : "r"(a), "r"(ph) : "memory");
  return ok;
}
__device__ __forceinline__ bool mbar_test(uint32_t a, uint32_t ph) {
  uint32_t ok;
  asm volatile("{\n.reg .pred p;\nmbarrier.test_wait.parity.shared::cta.b64 p,[%1],%2;\nselp.u32 %0,1,0,p;\n}" : "=r"(ok) : "r"(a), "r"(ph) : "memory");
  return ok;
}
constexpr int SPIN_LIMIT = 1 << 22;
__device__ __forceinline__ void mbar_wait(uint32_t a, uint32_t ph) {
  if (mbar_try(a, ph)) return;
  int n = 0;
  while (!mbar_try(a, ph)) { if (++n > SPIN_LIMIT) __trap(); }
}
__device__ __forceinline__ void bar_sync(int id, int n) { asm volatile("bar.sync %0,%1;" ::"r"(id), "r"(n) : "memory"); }
__device__ __forceinline__ void bar_arrive(int id, int n) { asm volatile("bar.arrive %0,%1;" ::"r"(id), "r"(n) : "memory"); }
__device__ __forceinline__ void st_async_b32(uint32_t a, uint32_t x, uint32_t mb) {
  asm volatile("st.async.weak.shared::cluster.mbarrier::complete_tx::bytes.b32 [%0],%1,[%2];" ::"r"(a), "r"(x), "r"(mb) : "memory");
}
__device__ __forceinline__ void st_async_v2(uint32_t a, uint32_t x, uint32_t y, uint32_t mb) {
  asm volatile("st.async.weak.shared::cluster.mbarrier::complete_tx::bytes.v2.b32 [%0],{%1,%2},[%3];" ::"r"(a), "r"(x), "r"(y), "r"(mb) : "memory");
}
__device__ __forceinline__ void ldsm4(uint32_t (&r)[4], uint32_t a) {
  asm volatile("ldmatrix.sync.aligned.m8n8.x4.shared.b16 {%0,%1,%2,%3},[%4];" : "=r"(r[0]), "=r"(r[1]), "=r"(r[2]), "=r"(r[3]) : "r"(a) : "memory");
}
__device__ __forceinline__ void ldsm2(uint32_t& r0, uint32_t& r1, uint32_t a) {
  asm volatile("ldmatrix.sync.aligned.m8n8.x2.shared.b16 {%0,%1},[%2];" : "=r"(r0), "=r"(r1) : "r"(a) : "memory");
}
__device__ __forceinline__ void ldsm4t(uint32_t (&r)[4], uint32_t a) {
  asm volatile("ldmatrix.sync.aligned.m8n8.x4.trans.shared.b16 {%0,%1,%2,%3},[%4];" : "=r"(r[0]), "=r"(r[1]), "=r"(r[2]), "=r"(r[3]) : "r"(a) : "memory");
}
__device__ __forceinline__ void stsm2t(uint32_t a, uint32_t r0, uint32_t r1) {
  asm volatile("stmatrix.sync.aligned.m8n8.x2.trans.shared.b16 [%0],{%1,%2};" ::"r"(a), "r"(r0), "r"(r1) : "memory");
}
__device__ __forceinline__ uint32_t movm(uint32_t a) {
  uint32_t d; asm volatile("movmatrix.sync.aligned.m8n8.trans.b16 %0,%1;" : "=r"(d) : "r"(a)); return d;
}
__device__ __forceinline__ void mma16816(float (&d)[4], const uint32_t (&a)[4], uint32_t b0, uint32_t b1) {
  asm volatile("mma.sync.aligned.m16n8k16.row.col.f32.bf16.bf16.f32 {%0,%1,%2,%3},{%4,%5,%6,%7},{%8,%9},{%0,%1,%2,%3};"
               : "+f"(d[0]), "+f"(d[1]), "+f"(d[2]), "+f"(d[3]) : "r"(a[0]), "r"(a[1]), "r"(a[2]), "r"(a[3]), "r"(b0), "r"(b1));
}
__device__ __forceinline__ uint32_t pack_bf16(float lo, float hi) {
  uint32_t r; asm("cvt.rn.bf16x2.f32 %0,%1,%2;" : "=r"(r) : "f"(hi), "f"(lo)); return r;
}
__device__ __forceinline__ float4 lds128f(uint32_t a) {
  float4 v; asm volatile("ld.shared.v4.f32 {%0,%1,%2,%3},[%4];" : "=f"(v.x), "=f"(v.y), "=f"(v.z), "=f"(v.w) : "r"(a) : "memory"); return v;
}
__device__ __forceinline__ uint4 lds128u(uint32_t a) {
  uint4 v; asm volatile("ld.shared.v4.u32 {%0,%1,%2,%3},[%4];" : "=r"(v.x), "=r"(v.y), "=r"(v.z), "=r"(v.w) : "r"(a) : "memory"); return v;
}
__device__ __forceinline__ float2 lds64f(uint32_t a) {
  float2 v; asm volatile("ld.shared.v2.f32 {%0,%1},[%2];" : "=f"(v.x), "=f"(v.y) : "r"(a) : "memory"); return v;
}
__device__ __forceinline__ void sts128f(uint32_t a, float x, float y, float z, float w) {
  asm volatile("st.shared.v4.f32 [%0],{%1,%2,%3,%4};" ::"r"(a), "f"(x), "f"(y), "f"(z), "f"(w) : "memory");
}
__device__ __forceinline__ void sts64f(uint32_t a, float x, float y) {
  asm volatile("st.shared.v2.f32 [%0],{%1,%2};" ::"r"(a), "f"(x), "f"(y) : "memory");
}
__device__ __forceinline__ void tma2d(uint32_t dst, const CUtensorMap* tm, int c0, int c1, uint32_t mb) {
  asm volatile("cp.async.bulk.tensor.2d.shared::cta.global.tile.mbarrier::complete_tx::bytes [%0],[%1,{%2,%3}],[%4];"
               ::"r"(dst), "l"(tm), "r"(c0), "r"(c1), "r"(mb) : "memory");
}
__device__ __forceinline__ uint32_t clock32() { uint32_t c; asm volatile("mov.u32 %0, %%clock;" : "=r"(c)); return c; }
__device__ __forceinline__ float ex2(float x) { float y; asm("ex2.approx.ftz.f32 %0,%1;" : "=f"(y) : "f"(x)); return y; }

__device__ __forceinline__ void tma2d_store(const CUtensorMap* tm, uint32_t src, int c0, int c1) {
  asm volatile("cp.async.bulk.tensor.2d.global.shared::cta.tile.bulk_group [%0,{%2,%3}],[%1];" ::"l"(tm), "r"(src), "r"(c0), "r"(c1) : "memory");
}
__device__ __forceinline__ void bulk_commit() { asm volatile("cp.async.bulk.commit_group;" ::: "memory"); }
__device__ __forceinline__ void bulk_wait_read0() { asm volatile("cp.async.bulk.wait_group.read 0;" ::: "memory"); }
__device__ __forceinline__ void bulk_wait0() { asm volatile("cp.async.bulk.wait_group 0;" ::: "memory"); }
__device__ __forceinline__ void fence_async_smem() { asm volatile("fence.proxy.async.shared::cta;" ::: "memory"); }
__device__ __forceinline__ void fence_async_all() { asm volatile("fence.proxy.async;" ::: "memory"); }
__device__ __forceinline__ void mbar_arrive(uint32_t a) { asm volatile("mbarrier.arrive.shared::cta.b64 _,[%0];" ::"r"(a) : "memory"); }
__device__ __forceinline__ void wg_fence() { asm volatile("wgmma.fence.sync.aligned;" ::: "memory"); }
__device__ __forceinline__ void wg_commit() { asm volatile("wgmma.commit_group.sync.aligned;" ::: "memory"); }
template <int N> __device__ __forceinline__ void wg_wait() { asm volatile("wgmma.wait_group.sync.aligned %0;" ::"n"(N) : "memory"); }
__device__ __forceinline__ uint64_t desc_k(uint32_t addr) {
  return (uint64_t)((addr & 0x3FFFF) >> 4) | ((uint64_t)1 << 16) | ((uint64_t)(1024 >> 4) << 32) | ((uint64_t)1 << 62);
}
__device__ __forceinline__ uint64_t desc_mn(uint32_t addr) {
  return (uint64_t)((addr & 0x3FFFF) >> 4) | ((uint64_t)(8192 >> 4) << 16) | ((uint64_t)(1024 >> 4) << 32) | ((uint64_t)1 << 62);
}
__device__ __forceinline__ void stsm4(uint32_t a, uint32_t r0, uint32_t r1, uint32_t r2, uint32_t r3) {
  asm volatile("stmatrix.sync.aligned.m8n8.x4.shared.b16 [%0],{%1,%2,%3,%4};" ::"r"(a), "r"(r0), "r"(r1), "r"(r2), "r"(r3) : "memory");
}
__device__ __forceinline__ unsigned ld_acquire(const unsigned* p) {
  unsigned v; asm volatile("ld.acquire.gpu.global.u32 %0,[%1];" : "=r"(v) : "l"(p) : "memory"); return v;
}
__device__ __forceinline__ void red_release(unsigned* p, unsigned v) {
  asm volatile("red.release.gpu.global.add.u32 [%0],%1;" ::"l"(p), "r"(v) : "memory");
}
__device__ __forceinline__ void wait_flag(const unsigned* p, unsigned target) {
  int n = 0;
  while (ld_acquire(p) < target) {
#define NSLEEP 64
    if (NSLEEP > 0) __nanosleep(NSLEEP);
    if (++n > (1 << 22)) __trap();
  }
}

__device__ __forceinline__ void bwait(uint32_t a, uint32_t ph) {
  asm volatile("{\n.reg .pred p;\n.reg .u32 n;\n"
               "mbarrier.try_wait.parity.shared::cta.b64 p,[%0],%1;\n@p bra.uni D;\nmov.u32 n,0;\n"
               "L: mbarrier.try_wait.parity.shared::cta.b64 p,[%0],%1;\n@p bra.uni D;\nadd.u32 n,n,1;\nsetp.lt.u32 p,n,4194304;\n@p bra.uni L;\ntrap;\n"
               "D:\n}" ::"r"(a), "r"(ph) : "memory");
}
__device__ __forceinline__ void arrive_if(bool c, uint32_t a) {
  asm volatile("{\n.reg .pred p;\nsetp.ne.u32 p,%1,0;\n@p mbarrier.arrive.shared::cta.b64 _,[%0];\n}" ::"r"(a), "r"((uint32_t)c) : "memory");
}
__device__ __forceinline__ void expect_if(bool c, uint32_t a, uint32_t tx) {
  asm volatile("{\n.reg .pred p;\nsetp.ne.u32 p,%2,0;\n@p mbarrier.arrive.expect_tx.shared::cta.b64 _,[%0],%1;\n}" ::"r"(a), "r"(tx), "r"((uint32_t)c) : "memory");
}
__device__ __forceinline__ void tma2d_if(bool c, uint32_t dst, const CUtensorMap* tm, int c0, int c1, uint32_t mb) {
  asm volatile("{\n.reg .pred p;\nsetp.ne.u32 p,%5,0;\n"
               "@p cp.async.bulk.tensor.2d.shared::cta.global.tile.mbarrier::complete_tx::bytes [%0],[%1,{%2,%3}],[%4];\n}"
               ::"r"(dst), "l"(tm), "r"(c0), "r"(c1), "r"(mb), "r"((uint32_t)c) : "memory");
}
__device__ __forceinline__ void publish_if(bool c, unsigned* flag) {
  asm volatile("{\n.reg .pred p;\nsetp.ne.u32 p,%1,0;\n@p cp.async.bulk.wait_group 0;\n@p fence.proxy.async;\n@p red.release.gpu.global.add.u32 [%0],1;\n}"
               ::"l"(flag), "r"((uint32_t)c) : "memory");
}

__device__ __forceinline__ void tma2d_prefetch(const CUtensorMap* tm, int c0, int c1) {
  asm volatile("cp.async.bulk.prefetch.tensor.2d.L2.global.tile [%0,{%1,%2}];" ::"l"(tm), "r"(c0), "r"(c1) : "memory");
}

__device__ __forceinline__ void wgmma_n256(float (&d)[128], uint64_t da, uint64_t db, int scale_d) {
  asm volatile("{\n.reg .pred p;\nsetp.ne.b32 p, %130, 0;\n"
    "wgmma.mma_async.sync.aligned.m64n256k16.f32.bf16.bf16 {%0,%1,%2,%3,%4,%5,%6,%7,%8,%9,%10,%11,%12,%13,%14,%15,%16,%17,%18,%19,%20,%21,%22,%23,%24,%25,%26,%27,%28,%29,%30,%31,%32,%33,%34,%35,%36,%37,%38,%39,%40,%41,%42,%43,%44,%45,%46,%47,%48,%49,%50,%51,%52,%53,%54,%55,%56,%57,%58,%59,%60,%61,%62,%63,%64,%65,%66,%67,%68,%69,%70,%71,%72,%73,%74,%75,%76,%77,%78,%79,%80,%81,%82,%83,%84,%85,%86,%87,%88,%89,%90,%91,%92,%93,%94,%95,%96,%97,%98,%99,%100,%101,%102,%103,%104,%105,%106,%107,%108,%109,%110,%111,%112,%113,%114,%115,%116,%117,%118,%119,%120,%121,%122,%123,%124,%125,%126,%127}, %128, %129, p, 1, 1, 0, 1;\n}"
    : "+f"(d[0]), "+f"(d[1]), "+f"(d[2]), "+f"(d[3]), "+f"(d[4]), "+f"(d[5]), "+f"(d[6]), "+f"(d[7]), "+f"(d[8]), "+f"(d[9]), "+f"(d[10]), "+f"(d[11]), "+f"(d[12]), "+f"(d[13]), "+f"(d[14]), "+f"(d[15]), "+f"(d[16]), "+f"(d[17]), "+f"(d[18]), "+f"(d[19]), "+f"(d[20]), "+f"(d[21]), "+f"(d[22]), "+f"(d[23]), "+f"(d[24]), "+f"(d[25]), "+f"(d[26]), "+f"(d[27]), "+f"(d[28]), "+f"(d[29]), "+f"(d[30]), "+f"(d[31]), "+f"(d[32]), "+f"(d[33]), "+f"(d[34]), "+f"(d[35]), "+f"(d[36]), "+f"(d[37]), "+f"(d[38]), "+f"(d[39]), "+f"(d[40]), "+f"(d[41]), "+f"(d[42]), "+f"(d[43]), "+f"(d[44]), "+f"(d[45]), "+f"(d[46]), "+f"(d[47]), "+f"(d[48]), "+f"(d[49]), "+f"(d[50]), "+f"(d[51]), "+f"(d[52]), "+f"(d[53]), "+f"(d[54]), "+f"(d[55]), "+f"(d[56]), "+f"(d[57]), "+f"(d[58]), "+f"(d[59]), "+f"(d[60]), "+f"(d[61]), "+f"(d[62]), "+f"(d[63]), "+f"(d[64]), "+f"(d[65]), "+f"(d[66]), "+f"(d[67]), "+f"(d[68]), "+f"(d[69]), "+f"(d[70]), "+f"(d[71]), "+f"(d[72]), "+f"(d[73]), "+f"(d[74]), "+f"(d[75]), "+f"(d[76]), "+f"(d[77]), "+f"(d[78]), "+f"(d[79]), "+f"(d[80]), "+f"(d[81]), "+f"(d[82]), "+f"(d[83]), "+f"(d[84]), "+f"(d[85]), "+f"(d[86]), "+f"(d[87]), "+f"(d[88]), "+f"(d[89]), "+f"(d[90]), "+f"(d[91]), "+f"(d[92]), "+f"(d[93]), "+f"(d[94]), "+f"(d[95]), "+f"(d[96]), "+f"(d[97]), "+f"(d[98]), "+f"(d[99]), "+f"(d[100]), "+f"(d[101]), "+f"(d[102]), "+f"(d[103]), "+f"(d[104]), "+f"(d[105]), "+f"(d[106]), "+f"(d[107]), "+f"(d[108]), "+f"(d[109]), "+f"(d[110]), "+f"(d[111]), "+f"(d[112]), "+f"(d[113]), "+f"(d[114]), "+f"(d[115]), "+f"(d[116]), "+f"(d[117]), "+f"(d[118]), "+f"(d[119]), "+f"(d[120]), "+f"(d[121]), "+f"(d[122]), "+f"(d[123]), "+f"(d[124]), "+f"(d[125]), "+f"(d[126]), "+f"(d[127])
    : "l"(da), "l"(db), "r"(scale_d));
}
__device__ __forceinline__ void wgmma_n128(float (&d)[64], uint64_t da, uint64_t db, int scale_d) {
  asm volatile("{\n.reg .pred p;\nsetp.ne.b32 p, %66, 0;\n"
    "wgmma.mma_async.sync.aligned.m64n128k16.f32.bf16.bf16 {%0,%1,%2,%3,%4,%5,%6,%7,%8,%9,%10,%11,%12,%13,%14,%15,%16,%17,%18,%19,%20,%21,%22,%23,%24,%25,%26,%27,%28,%29,%30,%31,%32,%33,%34,%35,%36,%37,%38,%39,%40,%41,%42,%43,%44,%45,%46,%47,%48,%49,%50,%51,%52,%53,%54,%55,%56,%57,%58,%59,%60,%61,%62,%63}, %64, %65, p, 1, 1, 0, 1;\n}"
    : "+f"(d[0]), "+f"(d[1]), "+f"(d[2]), "+f"(d[3]), "+f"(d[4]), "+f"(d[5]), "+f"(d[6]), "+f"(d[7]), "+f"(d[8]), "+f"(d[9]), "+f"(d[10]), "+f"(d[11]), "+f"(d[12]), "+f"(d[13]), "+f"(d[14]), "+f"(d[15]), "+f"(d[16]), "+f"(d[17]), "+f"(d[18]), "+f"(d[19]), "+f"(d[20]), "+f"(d[21]), "+f"(d[22]), "+f"(d[23]), "+f"(d[24]), "+f"(d[25]), "+f"(d[26]), "+f"(d[27]), "+f"(d[28]), "+f"(d[29]), "+f"(d[30]), "+f"(d[31]), "+f"(d[32]), "+f"(d[33]), "+f"(d[34]), "+f"(d[35]), "+f"(d[36]), "+f"(d[37]), "+f"(d[38]), "+f"(d[39]), "+f"(d[40]), "+f"(d[41]), "+f"(d[42]), "+f"(d[43]), "+f"(d[44]), "+f"(d[45]), "+f"(d[46]), "+f"(d[47]), "+f"(d[48]), "+f"(d[49]), "+f"(d[50]), "+f"(d[51]), "+f"(d[52]), "+f"(d[53]), "+f"(d[54]), "+f"(d[55]), "+f"(d[56]), "+f"(d[57]), "+f"(d[58]), "+f"(d[59]), "+f"(d[60]), "+f"(d[61]), "+f"(d[62]), "+f"(d[63])
    : "l"(da), "l"(db), "r"(scale_d));
}
__device__ __forceinline__ void wgmma_n64(float (&d)[32], uint64_t da, uint64_t db, int scale_d) {
  asm volatile("{\n.reg .pred p;\nsetp.ne.b32 p, %34, 0;\n"
    "wgmma.mma_async.sync.aligned.m64n64k16.f32.bf16.bf16 {%0,%1,%2,%3,%4,%5,%6,%7,%8,%9,%10,%11,%12,%13,%14,%15,%16,%17,%18,%19,%20,%21,%22,%23,%24,%25,%26,%27,%28,%29,%30,%31}, %32, %33, p, 1, 1, 0, 1;\n}"
    : "+f"(d[0]), "+f"(d[1]), "+f"(d[2]), "+f"(d[3]), "+f"(d[4]), "+f"(d[5]), "+f"(d[6]), "+f"(d[7]), "+f"(d[8]), "+f"(d[9]), "+f"(d[10]), "+f"(d[11]), "+f"(d[12]), "+f"(d[13]), "+f"(d[14]), "+f"(d[15]), "+f"(d[16]), "+f"(d[17]), "+f"(d[18]), "+f"(d[19]), "+f"(d[20]), "+f"(d[21]), "+f"(d[22]), "+f"(d[23]), "+f"(d[24]), "+f"(d[25]), "+f"(d[26]), "+f"(d[27]), "+f"(d[28]), "+f"(d[29]), "+f"(d[30]), "+f"(d[31])
    : "l"(da), "l"(db), "r"(scale_d));
}
namespace chain {
constexpr uint32_t OFF_A = 0;
constexpr uint32_t OFF_B = 81920;
constexpr uint32_t OFF_KX = 163840;
constexpr uint32_t OFF_MEM = 180224;
constexpr uint32_t OFF_O = 190464;
constexpr uint32_t OFF_QS = 198656;
constexpr uint32_t OFF_KS = 199680;
constexpr uint32_t OFF_VS = 201728;
constexpr uint32_t OFF_XB = 203776;
constexpr uint32_t OFF_XQ = 207872;
constexpr uint32_t OFF_SL = 209920;
constexpr uint32_t OFF_SR = 211200;
constexpr uint32_t OFF_RB = 212480;
constexpr uint32_t OFF_EXP = 214016;
constexpr uint32_t OFF_ZERO = 216064;
constexpr uint32_t OFF_BAR = 218624;
constexpr uint32_t OFF_PROF = OFF_BAR + 256;
constexpr uint32_t SMEM_BYTES = OFF_PROF + 1024;
static_assert(OFF_O % 1024 == 0 && OFF_BAR % 256 == 0, "alignment");
constexpr int B_MEM = 0, B_O = 8, B_PAIR = 16, B_TOK = 17, B_W = 19, NBAR = 24;
#define RING 10
static_assert(RING >= 8 && RING <= 12, "ring size");
#define POLL_DELAY 540

template <int P> __device__ __forceinline__ void twait(uint32_t a, uint32_t ph) {
  if (P == 0) asm volatile("mbarrier.try_wait.parity.shared::cta.b64 pw0,[%0],%1;" ::"r"(a), "r"(ph) : "memory");
  else if (P == 1) asm volatile("mbarrier.try_wait.parity.shared::cta.b64 pw1,[%0],%1;" ::"r"(a), "r"(ph) : "memory");
  else asm volatile("mbarrier.try_wait.parity.shared::cta.b64 pw2,[%0],%1;" ::"r"(a), "r"(ph) : "memory");
}
template <int P> __device__ __forceinline__ uint32_t gate(uint32_t a, uint32_t alt) {
  uint32_t r;
  if (P == 0) asm volatile("selp.u32 %0,%1,%2,pw0;\nand.pred pall, pall, pw0;" : "=r"(r) : "r"(a), "r"(alt));
  else if (P == 1) asm volatile("selp.u32 %0,%1,%2,pw1;\nand.pred pall, pall, pw1;" : "=r"(r) : "r"(a), "r"(alt));
  else asm volatile("selp.u32 %0,%1,%2,pw2;\nand.pred pall, pall, pw2;" : "=r"(r) : "r"(a), "r"(alt));
  return r;
}
__device__ __forceinline__ void pall_set() { asm volatile("setp.eq.u32 pall, 0, 0;"); }
__device__ __forceinline__ bool pall_get() { uint32_t r; asm volatile("selp.u32 %0,1,0,pall;" : "=r"(r)); return r != 0; }
__device__ __forceinline__ uint32_t junk() { uint32_t j; asm volatile("" : "=r"(j)); return j; }
__device__ __forceinline__ void mma_top(float (&d)[4], uint32_t a0, uint32_t a2, uint32_t b0, uint32_t b1) {
  const uint32_t j1 = junk(), j3 = junk();
  asm volatile("mma.sync.aligned.m16n8k16.row.col.f32.bf16.bf16.f32 {%0,%1,%2,%3},{%4,%5,%6,%7},{%8,%9},{%0,%1,%2,%3};"
               : "+f"(d[0]), "+f"(d[1]), "+f"(d[2]), "+f"(d[3]) : "r"(a0), "r"(j1), "r"(a2), "r"(j3), "r"(b0), "r"(b1));
}
__device__ __forceinline__ void mma_top8(float (&d)[4], uint32_t a0, uint32_t b0) {
  const uint32_t j1 = junk();
  asm volatile("mma.sync.aligned.m16n8k8.row.col.f32.bf16.bf16.f32 {%0,%1,%2,%3},{%4,%5},{%6},{%0,%1,%2,%3};"
               : "+f"(d[0]), "+f"(d[1]), "+f"(d[2]), "+f"(d[3]) : "r"(a0), "r"(j1), "r"(b0));
}

template <int KH> struct KMap {
  static constexpr __host__ __device__ int slot(int t) { return 2 * (t / 5) + KH; }
  static constexpr __host__ __device__ int kstep(int t) { return t % 5; }
  static constexpr __host__ __device__ uint32_t off(int t) { return (uint32_t)(slot(t) * 10240 + kstep(t) * 2048); }
  static constexpr int NG = 4;
  static constexpr __host__ __device__ int gfirst(int g) { return 5 * g; }
  static constexpr __host__ __device__ int gcount(int g) { return 5; }
};
template <int KH, int N>
__device__ __forceinline__ void load_tiles(uint32_t (&w)[N][4], uint32_t base) {
#pragma unroll
  for (int t = 0; t < N; t++) ldsm4t(w[t], base + KMap<KH>::off(t));
}

template <int KH>
__device__ __forceinline__ void phase_q(const uint32_t (&wq)[20][4], const uint32_t (&wk)[20][4], uint32_t (&dyn)[RING][4],
                                        float (&aq)[4], float (&ak)[4], float (&av)[4], uint32_t l16, uint32_t bar, uint32_t vbase, int s) {
  using KM = KMap<KH>;
#pragma unroll
  for (int i = 0; i < 4; i++) aq[i] = ak[i] = av[i] = 0.f;
  const uint32_t par = (s - 1) & 1;
  pall_set();
  uint32_t bb[2][10];
  twait<0>(bar + (B_MEM + KM::slot(0)) * 8, par);
#pragma unroll
  for (int g = -1; g < KM::NG; g++) {
    if (g + 1 < KM::NG) {
      const int n = g + 1, t0 = KM::gfirst(n), cnt = KM::gcount(n);
      const uint32_t a = ((n & 1) ? gate<1>(l16, bar - OFF_BAR) : gate<0>(l16, bar - OFF_BAR)) + OFF_MEM + KM::slot(t0) * 1280 + KM::kstep(t0) * 256;
      uint32_t t4[4];
      ldsm4(t4, a); bb[n & 1][0] = t4[0]; bb[n & 1][1] = t4[1]; bb[n & 1][2] = t4[2]; bb[n & 1][3] = t4[3];
      if (cnt >= 4) { ldsm4(t4, a + 512); bb[n & 1][4] = t4[0]; bb[n & 1][5] = t4[1]; bb[n & 1][6] = t4[2]; bb[n & 1][7] = t4[3]; }
      if (cnt == 3) ldsm2(bb[n & 1][4], bb[n & 1][5], a + 512);
      if (cnt == 5) ldsm2(bb[n & 1][8], bb[n & 1][9], a + 1024);
      if (n + 1 < KM::NG) {
        if (n & 1) twait<0>(bar + (B_MEM + KM::slot(KM::gfirst(n + 1))) * 8, par); else twait<1>(bar + (B_MEM + KM::slot(KM::gfirst(n + 1))) * 8, par);
      }
    }
    if (g >= 0) {
#pragma unroll
      for (int i = 0; i < KM::gcount(g); i++) {
        const int t = KM::gfirst(g) + i;
        mma16816(aq, wq[t], bb[g & 1][2 * i], bb[g & 1][2 * i + 1]);
        mma16816(ak, wk[t], bb[g & 1][2 * i], bb[g & 1][2 * i + 1]);
        mma16816(av, dyn[t % RING], bb[g & 1][2 * i], bb[g & 1][2 * i + 1]);
        if (t + RING < 20) ldsm4t(dyn[t % RING], vbase + KM::off(t + RING));
      }
    }
  }
  if (!pall_get()) {
#pragma unroll 1
    for (int j = 0; j < 8; j++) mbar_wait(bar + (B_MEM + j) * 8, par);
#pragma unroll
    for (int i = 0; i < 4; i++) aq[i] = ak[i] = av[i] = 0.f;
#pragma unroll
    for (int t = 0; t < 20; t++) {
      uint32_t b0, b1, a[4];
      ldsm2(b0, b1, l16 + OFF_MEM + KM::slot(t) * 1280 + KM::kstep(t) * 256);
      ldsm4t(a, vbase + KM::off(t));
      mma16816(aq, wq[t], b0, b1);
      mma16816(ak, wk[t], b0, b1);
      mma16816(av, a, b0, b1);
    }
  }
}

__device__ __forceinline__ void fetch_first_tokens(uint4 (&xr)[4][3], const bf16* __restrict__ x, int tid, int rank) {
#pragma unroll
  for (int nu = 0; nu < 4; nu++)
#pragma unroll
    for (int q = 0; q < 3; q++) {
      const int p = tid + q * 256, i = p & 7, ch = p >> 3;
      xr[nu][q] = p < 640 ? __ldg(reinterpret_cast<const uint4*>(x + (nu * 8 + i) * D_ + (rank ^ (ch / 10)) * 80 + (ch % 10) * 8)) : make_uint4(0, 0, 0, 0);
    }
}
template <int KH>
__device__ __forceinline__ void first_tokens(const uint32_t (&wk)[20][4], const uint4 (&xr)[4][3], uint32_t sb, uint32_t l16, uint32_t lp, int tid,
                                             int lane, int pw) {
  using KM = KMap<KH>;
#pragma unroll
  for (int nu = 0; nu < 4; nu++) {
    bar_sync(0, 256);
#pragma unroll
    for (int q = 0; q < 3; q++) {
      const int p = tid + q * 256, i = p & 7, ch = p >> 3;
      if (p < 640) asm volatile("st.shared.v4.u32 [%0],{%1,%2,%3,%4};" ::"r"(sb + OFF_MEM + ch * 128 + i * 16), "r"(xr[nu][q].x), "r"(xr[nu][q].y), "r"(xr[nu][q].z), "r"(xr[nu][q].w) : "memory");
    }
    bar_sync(0, 256);
    float ak[4] = {0.f, 0.f, 0.f, 0.f}, av[4] = {0.f, 0.f, 0.f, 0.f};
#pragma unroll
    for (int t = 0; t < 20; t++) {
      uint32_t b0, b1, a[4];
      ldsm2(b0, b1, l16 + OFF_MEM + KM::slot(t) * 1280 + KM::kstep(t) * 256);
      ldsm4t(a, lp + OFF_A + KM::off(t));
      mma16816(ak, wk[t], b0, b1);
      mma16816(av, a, b0, b1);
    }
    if (KH == 0) {
      sts128f(l16 + OFF_XB + pw * 1024, ak[0], ak[1], ak[2], ak[3]);
      sts128f(l16 + OFF_XB + pw * 1024 + 512, av[0], av[1], av[2], av[3]);
      bar_sync(1 + pw, 64);
    } else {
      bar_sync(1 + pw, 64);
      const float4 o = lds128f(l16 + OFF_XB + pw * 1024), u = lds128f(l16 + OFF_XB + pw * 1024 + 512);
      const int r = lane & 7;
      const uint32_t dst = sb + OFF_KX + (nu * 8 + r) * 128 + (((2 * pw + ((lane >> 3) & 1)) ^ r) << 4);
      stsm2t(dst, pack_bf16(ak[0] + o.x, ak[1] + o.y), pack_bf16(ak[2] + o.z, ak[3] + o.w));
      stsm2t(dst + 4096, pack_bf16(av[0] + u.x, av[1] + u.y), pack_bf16(av[2] + u.z, av[3] + u.w));
    }
  }
  fence_async_smem();
  bar_sync(0, 256);
}

struct GlobRet { float a0, a1, a2, an, b0, bn; };
__device__ __forceinline__ void glob_red(const float (&c)[4], int idx, GlobRet& r) {
  asm volatile("red.relaxed.gpu.global.add.v4.f32 [%0],{%1,%2,%3,%4};" ::"l"(g_acc4 + idx * 4), "f"(c[0]), "f"(c[1]), "f"(c[2]), "f"(1.0f) : "memory");
  asm volatile("red.relaxed.gpu.global.add.v2.f32 [%0],{%1,%2};" ::"l"(g_acc2 + idx * 2), "f"(c[3]), "f"(1.0f) : "memory");
}
__device__ __forceinline__ void glob_poll(uint32_t t_start, int idx, uint32_t dst, uint32_t bar, const GlobRet& r, const float (&c)[4]
) {
  const float* p4 = g_acc4 + idx * 4;
  const float* p2 = g_acc2 + idx * 2;
  float a0, a1, a2, an, b0, bn;
  int n = 0;
  bool done = false;
  while (clock32() - t_start < (uint32_t)POLL_DELAY) {}
  while (!done) {
    asm volatile("ld.relaxed.gpu.global.v4.f32 {%0,%1,%2,%3},[%4];" : "=f"(a0), "=f"(a1), "=f"(a2), "=f"(an) : "l"(p4) : "memory");
    asm volatile("ld.relaxed.gpu.global.v2.f32 {%0,%1},[%2];" : "=f"(b0), "=f"(bn) : "l"(p2) : "memory");
    ++n;
    if (__all_sync(0xffffffffu, an >= 8.0f && bn >= 8.0f)) break;
    if (n > SPIN_LIMIT) __trap();
  }
  const uint32_t t0 = movm(pack_bf16(a0, a1)), t1 = movm(pack_bf16(a2, b0));
#pragma unroll
  for (int d = 1; d < 8; d++) {
    const uint32_t ra = (dst ^ (d << 24)) + d * 1280, rb = (bar ^ (d << 24)) + (B_MEM + d) * 8;
    st_async_b32(ra, t0, rb);
    st_async_b32(ra + 128, t1, rb);
  }
  asm volatile("st.shared.u32 [%0],%1;" ::"r"(dst), "r"(t0) : "memory");
  asm volatile("st.shared.u32 [%0],%1;" ::"r"(dst + 128), "r"(t1) : "memory");
  __syncwarp();
  arrive_if((threadIdx.x & 31) == 0, bar + B_MEM * 8);
}

__device__ __forceinline__ void chain_role(const CUtensorMap& tmWq, const CUtensorMap& tmWk, const CUtensorMap& tmWv,
                                           const CUtensorMap& tmWo, const CUtensorMap& tmWo4, const CUtensorMap& tmKV, const CUtensorMap& tmKVM,
                                           const bf16* __restrict__ mem0, const bf16* __restrict__ x, uint8_t* smem_raw) {
  asm volatile(".reg .pred pw0, pw1, pw2, pall;");
  uint32_t rank_u; asm("mov.u32 %0, %%cluster_ctarank;" : "=r"(rank_u));
  const int rank = (int)rank_u;
  const uint32_t sb = mapa((smem_u32(smem_raw) + 1023) & ~1023u, rank_u);
  const int tid = threadIdx.x;
  int lane; asm volatile("mov.u32 %0, %%laneid;" : "=r"(lane));
  const int warp = __shfl_sync(0xffffffffu, tid >> 5, 0);
  const int cl = blockIdx.x >> 3;
  const int head = cl * 4 + (rank >> 1), hf = rank & 1;
  const int col0 = head * 128 + hf * 64;
  const int pw = warp & 3;
  const uint32_t bar = sb + OFF_BAR;

  if (tid == 0) {
    for (int i = 0; i < NBAR; i++) mbar_init(bar + i * 8, i == B_MEM ? 5 : (i == B_O ? 4 : 1));
    asm volatile("fence.mbarrier_init.release.cluster;" ::: "memory");
    asm volatile("fence.proxy.async.shared::cta;" ::: "memory");
    mbar_expect(bar + (B_W + 1) * 8, 81920);
    mbar_expect(bar + (B_W + 3) * 8, 81920);
    for (int b = 0; b < 8; b++) {
      tma2d(sb + OFF_B + (rank ^ b) * 10240, &tmWk, col0, b * 80, bar + (B_W + 1) * 8);
      tma2d(sb + OFF_A + (rank ^ b) * 10240, &tmWv, col0, b * 80, bar + (B_W + 3) * 8);
    }
    for (int j = 1; j < 8; j++) { mbar_expect(bar + (B_MEM + j) * 8, 1280); mbar_expect(bar + (B_O + j) * 8, 1024); }
    mbar_expect(bar + B_PAIR * 8, 1280);
  }
  if (tid < 160) asm volatile("st.shared.v4.u32 [%0],{%1,%1,%1,%1};" ::"r"(sb + OFF_ZERO + tid * 16), "r"(0) : "memory");
  fence_async_smem();
  __syncthreads();
  asm volatile("barrier.cluster.arrive.release.aligned;" ::: "memory");

  const int q4 = lane >> 3, rr = lane & 7;
  const uint32_t lp = sb + ((q4 >> 1) * 8 + rr) * 128 + (((2 * pw + (q4 & 1)) ^ rr) << 4);
  const uint32_t l16 = sb + lane * 16, l8 = sb + lane * 8;

  uint32_t wq[20][4], wk[20][4];
  uint4 xr[4][3];
  fetch_first_tokens(xr, x, tid, rank);
  uint4 m0[3];
#pragma unroll
  for (int q = 0; q < 3; q++) {
    const int p = tid + q * 256, i = p & 7, ch = p >> 3;
    m0[q] = p < 640 ? __ldg(reinterpret_cast<const uint4*>(mem0 + i * 640 + (rank ^ (ch / 10)) * 80 + (ch % 10) * 8)) : make_uint4(0, 0, 0, 0);
  }
  mbar_wait(bar + (B_W + 1) * 8, 0);
  if (warp < 4) load_tiles<0, 20>(wk, lp + OFF_B); else load_tiles<1, 20>(wk, lp + OFF_B);
  __syncthreads();
  if (tid == 0) {
    mbar_expect(bar + (B_W + 0) * 8, 81920);
    for (int j = 0; j < 8; j++) tma2d(sb + OFF_B + j * 10240, &tmWq, col0, (rank ^ j) * 80, bar + (B_W + 0) * 8);
  }
  mbar_wait(bar + (B_W + 3) * 8, 0);
  if (warp < 4) first_tokens<0>(wk, xr, sb, l16, lp, tid, lane, pw); else first_tokens<1>(wk, xr, sb, l16, lp, tid, lane, pw);
#pragma unroll
  for (int q = 0; q < 3; q++) {
    const int p = tid + q * 256, i = p & 7, ch = p >> 3;
    if (p < 640) asm volatile("st.shared.v4.u32 [%0],{%1,%2,%3,%4};" ::"r"(sb + OFF_MEM + ch * 128 + i * 16), "r"(m0[q].x), "r"(m0[q].y), "r"(m0[q].z), "r"(m0[q].w) : "memory");
  }
  if (tid == 0) mbar_arrive(bar + B_TOK * 8);
  mbar_wait(bar + (B_W + 0) * 8, 0);
  if (warp < 4) load_tiles<0, 20>(wq, lp + OFF_B); else load_tiles<1, 20>(wq, lp + OFF_B);
  __syncthreads();
  if (tid == 0) {
    mbar_expect(bar + (B_W + 4) * 8, 65536);
    for (int j = 0; j < 8; j++) tma2d(sb + OFF_B + j * 8192, &tmWo, rank * 80, cl * 512 + (rank ^ j) * 64, bar + (B_W + 4) * 8);
    mbar_expect(bar + (B_W + 2) * 8, 16384);
    for (int j = 0; j < 8; j++) tma2d(sb + OFF_B + 65536 + j * 2048, &tmWo4, rank * 80 + 64, cl * 512 + (rank ^ j) * 64, bar + (B_W + 2) * 8);
  }
  asm volatile("barrier.cluster.wait.acquire.aligned;" ::: "memory");

  if (warp < 4) {
    uint32_t dyn[RING][4];
    mbar_wait(bar + (B_W + 3) * 8, 0);
    load_tiles<0, RING>(dyn, lp + OFF_A);

    for (int s = 0; s < NSEG; s++) {
      const int par = s & 1;
      float aq[4], ak[4], av[4];
      phase_q<0>(wq, wk, dyn, aq, ak, av, l16, bar, lp + OFF_A, s);
      sts128f(l16 + OFF_XB + pw * 1024, ak[0], ak[1], ak[2], ak[3]);
      sts128f(l16 + OFF_XB + pw * 1024 + 512, av[0], av[1], av[2], av[3]);
      bar_sync(1 + pw, 64);
      {
        const float4 o = lds128f(l16 + OFF_XQ + pw * 512);
        stsm2t(sb + (lane & 15) * 16 + OFF_QS + 2 * pw * 128, pack_bf16(aq[0] + o.x, aq[1] + o.y), pack_bf16(aq[2] + o.z, aq[3] + o.w));
      }
      bar_sync(0, 256);
      if (s == NSEG - 1) break;
      if (pw == 0 && s != NSEG - 1) {
        uint32_t qa[4][4], km[2][4];
        const uint32_t qadr = sb + OFF_QS + (lane >> 4) * 128 + (lane & 7) * 16;
#pragma unroll
        for (int k = 0; k < 4; k++) ldsm4(qa[k], qadr + k * 256);
        ldsm4(km[0], l16 + OFF_KS + par * 1024);
        ldsm4(km[1], l16 + OFF_KS + par * 1024 + 512);
        float m0[4] = {0.f, 0.f, 0.f, 0.f}, m1[4] = {0.f, 0.f, 0.f, 0.f};
        mma16816(m0, qa[0], km[0][0], km[0][1]);
        mma16816(m1, qa[2], km[1][0], km[1][1]);
        mma16816(m0, qa[1], km[0][2], km[0][3]);
        mma16816(m1, qa[3], km[1][2], km[1][3]);
        const float mx = m0[0] + m1[0], my = m0[1] + m1[1];
        st_async_v2((l8 + OFF_SR) ^ (1 << 24), __float_as_uint(mx), __float_as_uint(my), (bar + B_PAIR * 8) ^ (1 << 24));
        sts64f(l8 + OFF_SL, mx, my);
        bar_arrive(5, 160);
      }
      bar_sync(6, 256);
      if (s == 0) mbar_wait(bar + (B_W + 4) * 8, 0);
#pragma unroll
      for (int t = 0; t < RING; t++) ldsm4t(dyn[t], lp + OFF_B + t * 2048);
      float c0[4] = {0.f, 0.f, 0.f, 0.f}, c1[4] = {0.f, 0.f, 0.f, 0.f};
      {
        constexpr int OLATE = 3;
        uint32_t b[3][2][4];
        pall_set();
        twait<0>(bar + B_O * 8, par);
        uint32_t gl = l16;
#pragma unroll
        for (int j = -1; j < 8; j++) {
          if (j < 7) {
            const int n = j + 1;
            if (n < OLATE) {
              gl = (n & 1) ? gate<1>(l16, bar - OFF_BAR) : gate<0>(l16, bar - OFF_BAR);
              if (n + 1 < OLATE) { if (n & 1) twait<0>(bar + (B_O + n + 1) * 8, par); else twait<1>(bar + (B_O + n + 1) * 8, par); }
            } else if (n == OLATE) {
#pragma unroll
              for (int q = OLATE; q < 8; q++) { twait<2>(bar + (B_O + q) * 8, par); gl = gate<2>(gl, bar - OFF_BAR); }
            }
            const uint32_t a = gl + OFF_O + n * 1024;
            ldsm4(b[n % 3][0], a); ldsm4(b[n % 3][1], a + 512);

          }
          if (j >= 0) {
            const int p = j % 3;
#pragma unroll
            for (int k = 0; k < 4; k++) {
              const int t = 4 * j + k;
              if (k & 1) mma16816(c1, dyn[t % RING], b[p][k >> 1][2], b[p][k >> 1][3]); else mma16816(c0, dyn[t % RING], b[p][k >> 1][0], b[p][k >> 1][1]);
              if (t + RING < 32) ldsm4t(dyn[t % RING], lp + OFF_B + (t + RING) * 2048);
            }
          }
        }
        if (!pall_get()) {
#pragma unroll 1
          for (int j = 0; j < 8; j++) mbar_wait(bar + (B_O + j) * 8, par);
#pragma unroll
          for (int i = 0; i < 4; i++) c0[i] = c1[i] = 0.f;
#pragma unroll 1
          for (int t = 0; t < 32; t++) {
            uint32_t b0, b1, a[4];
            ldsm2(b0, b1, l16 + OFF_O + t * 256);
            ldsm4t(a, lp + OFF_B + t * 2048);
            mma16816(c0, a, b0, b1);
          }
        }
      }
      bar_arrive(9, 224);
#pragma unroll
      for (int i = 0; i < 4; i++) c0[i] += c1[i];
      const int idx = ((s & 7) * 8 + rank) * 160 + pw * 32 + lane;
      GlobRet gr;
      glob_red(c0, idx, gr);
      const uint32_t t_start = clock32();
      load_tiles<0, RING>(dyn, lp + OFF_A);
      glob_poll(t_start, idx, sb + OFF_MEM + pw * 256 + lane * 4, bar, gr, c0
      );
    }
  } else {
    uint32_t dyn[RING][4];
    mbar_wait(bar + (B_W + 3) * 8, 0);
    load_tiles<1, RING>(dyn, lp + OFF_A);
    __syncwarp();
    bool tok_pending = true;
    const float sl2 = 0.08838834764831845f * 1.4426950408889634f;

    for (int s = 0; s < NSEG; s++) {
      const int par = s & 1;
      const bool last = (s == NSEG - 1);
      const bool tok_ready = last || mbar_test(bar + (B_TOK + par) * 8, (s >> 1) & 1);
      float aq[4], ak[4], av[4];
      phase_q<1>(wq, wk, dyn, aq, ak, av, l16, bar, lp + OFF_A, s);
      sts128f(l16 + OFF_XQ + pw * 512, aq[0], aq[1], aq[2], aq[3]);
      const uint32_t kxb = sb + OFF_KX + par * 8192;
      bar_sync(1 + pw, 64);
      uint32_t vm0, vm1;
      {
        const float4 o = lds128f(l16 + OFF_XB + pw * 1024);
        stsm2t(sb + (lane & 15) * 16 + OFF_KS + par * 1024 + 2 * pw * 128, pack_bf16(ak[0] + o.x, ak[1] + o.y), pack_bf16(ak[2] + o.z, ak[3] + o.w));
        const float4 u = lds128f(l16 + OFF_XB + pw * 1024 + 512);
        vm0 = pack_bf16(av[0] + u.x, av[1] + u.y);
        vm1 = pack_bf16(av[2] + u.z, av[3] + u.w);
      }
      bar_sync(0, 256);
      if (!last) {
        float sc[5][2];
        uint32_t vx[2][4];
        {
          if (!tok_ready) bwait(bar + (B_TOK + par) * 8, (s >> 1) & 1);
          uint32_t kx[2][4], qa[4][4];
          const uint32_t ka = kxb + (pw * 8 + rr) * 128;
          const uint32_t qadr = sb + OFF_QS + (lane >> 4) * 128 + (lane & 7) * 16;
          ldsm4(qa[0], qadr);
          ldsm4(kx[0], ka + ((q4 ^ rr) << 4));
          ldsm4(qa[2], qadr + 512);
          ldsm4(kx[1], ka + (((4 + q4) ^ rr) << 4));
          ldsm4(qa[1], qadr + 256);
          ldsm4(qa[3], qadr + 768);
          float t0[4] = {0.f, 0.f, 0.f, 0.f}, t1[4] = {0.f, 0.f, 0.f, 0.f};
          mma16816(t0, qa[0], kx[0][0], kx[0][1]);
          mma16816(t1, qa[2], kx[1][0], kx[1][1]);
          mma16816(t0, qa[1], kx[0][2], kx[0][3]);
          mma16816(t1, qa[3], kx[1][2], kx[1][3]);
          const float tx = t0[0] + t1[0], ty = t0[1] + t1[1];
          st_async_v2((l8 + OFF_SR + (pw + 1) * 256) ^ (1 << 24), __float_as_uint(tx), __float_as_uint(ty), (bar + B_PAIR * 8) ^ (1 << 24));
          sts64f(l8 + OFF_SL + (pw + 1) * 256, tx, ty);
        }
        bar_arrive(6, 256);
        if (warp == 6 && lane < 8 && lane > 0 && s > 0) mbar_expect(bar + (B_MEM + lane) * 8, 1280);
        {
          const uint32_t va = kxb + 4096 + lane * 128;
          ldsm4t(vx[0], va + (((2 * pw) ^ rr) << 4));
          ldsm4t(vx[1], va + (((2 * pw + 1) ^ rr) << 4));
        }
        bar_sync(5, 160);
#pragma unroll
        for (int n = 0; n < 5; n++) { const float2 v = lds64f(l8 + OFF_SL + n * 256); sc[n][0] = v.x; sc[n][1] = v.y; }
        bwait(bar + B_PAIR * 8, par);
#pragma unroll
        for (int n = 0; n < 5; n++) { const float2 v = lds64f(l8 + OFF_SR + n * 256); sc[n][0] += v.x; sc[n][1] += v.y; }
        float mxv = fmaxf(fmaxf(fmaxf(sc[0][0], sc[0][1]), fmaxf(sc[1][0], sc[1][1])), fmaxf(fmaxf(sc[2][0], sc[2][1]), fmaxf(sc[3][0], sc[3][1])));
        mxv = fmaxf(mxv, fmaxf(sc[4][0], sc[4][1]));
        mxv = fmaxf(mxv, __shfl_xor_sync(0xffffffffu, mxv, 1));
        mxv = fmaxf(mxv, __shfl_xor_sync(0xffffffffu, mxv, 2));
        const float off = -mxv * sl2;
        uint32_t p[5];
        float sum = 0.f;
#pragma unroll
        for (int n = 0; n < 5; n++) {
          const float e0 = ex2(fmaf(sc[n][0], sl2, off)), e1 = ex2(fmaf(sc[n][1], sl2, off));
          p[n] = pack_bf16(e0, e1);
          sum += e0 + e1;
        }
        float o0[4] = {0.f, 0.f, 0.f, 0.f}, o1[4] = {0.f, 0.f, 0.f, 0.f};
        mma_top(o0, p[0], p[1], vm0, vx[0][0]);
        mma_top(o1, p[0], p[1], vm1, vx[1][0]);
        mma_top(o0, p[2], p[3], vx[0][1], vx[0][2]);
        mma_top(o1, p[2], p[3], vx[1][1], vx[1][2]);
        mma_top8(o0, p[4], vx[0][3]);
        mma_top8(o1, p[4], vx[1][3]);
        sum += __shfl_xor_sync(0xffffffffu, sum, 1);
        sum += __shfl_xor_sync(0xffffffffu, sum, 2);
        float inv; asm("rcp.approx.ftz.f32 %0,%1;" : "=f"(inv) : "f"(sum));
        const uint32_t ob0 = pack_bf16(o0[0] * inv, o0[1] * inv), ob1 = pack_bf16(o1[0] * inv, o1[1] * inv);
        const uint32_t dst = sb + lane * 4 + OFF_O + pw * 256, ob = bar + B_O * 8;
#pragma unroll
        for (int d = 1; d < 8; d++) {
          const uint32_t ra = (dst ^ (d << 24)) + d * 1024, rb = ob ^ (d * 8 | d << 24);
          st_async_b32(ra, ob0, rb);
          st_async_b32(ra + 128, ob1, rb);
        }
        asm volatile("st.shared.u32 [%0],%1;" ::"r"(dst), "r"(ob0) : "memory");
        asm volatile("st.shared.u32 [%0],%1;" ::"r"(dst + 128), "r"(ob1) : "memory");
        __syncwarp();
        arrive_if(lane == 0, ob);
        if (s == 0) mbar_wait(bar + (B_W + 2) * 8, 0);
        {
          const int r8 = (q4 >> 1) * 8 + rr;
          const uint32_t o4 = sb + OFF_B + 65536 + (2 * pw * 64 + r8) * 32 + (((q4 & 1) ^ ((rr >> 2) & 1)) << 4);
#pragma unroll
          for (int t = 0; t < 8; t++) ldsm4t(dyn[t], o4 + ((t >> 2) * 64 + 16 * (t & 3)) * 32);
        }
        if (warp == 6 && lane == 0) mbar_expect(bar + B_PAIR * 8, 1280);
      }
      stsm2t(sb + (lane & 15) * 16 + OFF_VS + par * 1024 + 2 * pw * 128, vm0, vm1);
      bar_sync(7, 128);
      if (!last) {
        float c0[4] = {0.f, 0.f, 0.f, 0.f}, c1[4] = {0.f, 0.f, 0.f, 0.f};
#pragma unroll
        for (int jj = 0; jj < 2; jj++) {
          const uint32_t joff = (2 * pw + jj) * 1024;
          bwait(bar + (B_O + 2 * pw + jj) * 8, par);
          uint32_t b[2][4];
          ldsm4(b[0], l16 + OFF_O + joff);
          ldsm4(b[1], l16 + OFF_O + joff + 512);
          mma16816(c0, dyn[4 * jj], b[0][0], b[0][1]); mma16816(c1, dyn[4 * jj + 1], b[0][2], b[0][3]);
          mma16816(c0, dyn[4 * jj + 2], b[1][0], b[1][1]); mma16816(c1, dyn[4 * jj + 3], b[1][2], b[1][3]);
        }
#pragma unroll
        for (int i = 0; i < 4; i++) c0[i] += c1[i];
        if (pw < 3) {
          sts128f(l16 + OFF_RB + pw * 512, c0[0], c0[1], c0[2], c0[3]);
          bar_arrive(8, 128);
          bar_sync(9, 224);
          load_tiles<1, RING>(dyn, lp + OFF_A);
        } else {
          bar_sync(8, 128);
          const float4 r0 = lds128f(l16 + OFF_RB), r1 = lds128f(l16 + OFF_RB + 512), r2 = lds128f(l16 + OFF_RB + 1024);
          c0[0] += (r0.x + r1.x) + r2.x; c0[1] += (r0.y + r1.y) + r2.y; c0[2] += (r0.z + r1.z) + r2.z; c0[3] += (r0.w + r1.w) + r2.w;
          const int idx = ((s & 7) * 8 + rank) * 160 + 128 + lane;
          GlobRet gr;
          glob_red(c0, idx, gr);
          const uint32_t t_start = clock32();
          load_tiles<1, RING>(dyn, lp + OFF_A);
          glob_poll(t_start, idx, sb + OFF_MEM + 4 * 256 + lane * 4, bar, gr, c0
      );
        }
      }
      if (pw == 0) {
        if (lane == 0 && s > 0) {
          bulk_wait0();
          asm volatile("red.relaxed.gpu.global.add.u32 [%0],1;" ::"l"(&g_flags.mem[s - 1]) : "memory");
        }
        __syncwarp();
        if (last) {
          bf16* gk = g_KVM + ((size_t)(s * H_ + head) * 2) * 1024 + hf * 64;
#pragma unroll
          for (int it = 0; it < 2; it++) {
            const int j = lane & 7, ch = it * 4 + (lane >> 3);
            __stcg(reinterpret_cast<uint4*>(gk + j * 128 + ch * 8), lds128u(sb + OFF_KS + par * 1024 + ch * 128 + j * 16));
            __stcg(reinterpret_cast<uint4*>(gk + 1024 + j * 128 + ch * 8), lds128u(sb + OFF_VS + par * 1024 + ch * 128 + j * 16));
          }
          __threadfence();
          __syncwarp();
          if (lane == 0) asm volatile("red.relaxed.gpu.global.add.u32 [%0],1;" ::"l"(&g_flags.mem[s]) : "memory");
        } else {
#pragma unroll
          for (int it = 0; it < 2; it++) {
            const int j = lane & 7, ch = it * 4 + (lane >> 3);
            const uint4 kv = lds128u(sb + OFF_KS + par * 1024 + ch * 128 + j * 16);
            const uint4 vv = lds128u(sb + OFF_VS + par * 1024 + ch * 128 + j * 16);
            const uint32_t dst = sb + OFF_EXP + j * 128 + ((ch ^ j) << 4);
            asm volatile("st.shared.v4.u32 [%0],{%1,%2,%3,%4};" ::"r"(dst), "r"(kv.x), "r"(kv.y), "r"(kv.z), "r"(kv.w) : "memory");
            asm volatile("st.shared.v4.u32 [%0],{%1,%2,%3,%4};" ::"r"(dst + 1024), "r"(vv.x), "r"(vv.y), "r"(vv.z), "r"(vv.w) : "memory");
          }
          fence_async_smem();
          __syncwarp();
          if (lane == 0) {
            tma2d_store(&tmKVM, sb + OFF_EXP, hf * 64, (s * H_ + head) * 16);
            bulk_commit();
          }
        }
        __syncwarp();
      } else if (pw == 1) {
        if (!last) {
          if (lane < 8) { mbar_wait(bar + (B_O + lane) * 8, par); if (lane > 0) mbar_expect(bar + (B_O + lane) * 8, 1024); }
          __syncwarp();
          if (lane == 0) {
            auto request = [&](int seg) {
              const uint32_t kb = sb + OFF_KX + (seg & 1) * 8192, tb = bar + (B_TOK + (seg & 1)) * 8;
              mbar_expect(tb, 8192);
              tma2d(kb, &tmKV, col0, seg * 32, tb);
              tma2d(kb + 4096, &tmKV, 4096 + col0, seg * 32, tb);
            };
            if (tok_pending) {
              wait_flag(&g_flags.kv[(s + 1) >> 2], 64);
              fence_async_all();
              request(s + 1);
              tok_pending = false;
            }
            if (s + 2 < NSEG - 1) {
              if (((s + 2) & 3) == 0) {
                if (ld_acquire(&g_flags.kv[(s + 2) >> 2]) >= 64) fence_async_all(); else tok_pending = true;
              }
              if (!tok_pending) request(s + 2);
            }
          }
          __syncwarp();
        }
      } else if (pw == 2) {
        if (lane == 0) {
          bulk_wait0();
          if (cl == (s & 7)) {
            const int base = (((s + 3) & 7) * 8 + rank) * 160;
            asm volatile("cp.async.bulk.global.shared::cta.bulk_group [%0],[%1],2560;" ::"l"(g_acc4 + base * 4), "r"(sb + OFF_ZERO) : "memory");
            asm volatile("cp.async.bulk.global.shared::cta.bulk_group [%0],[%1],1280;" ::"l"(g_acc2 + base * 2), "r"(sb + OFF_ZERO) : "memory");
            bulk_commit();
            if (last) bulk_wait0();
          }
        }
        __syncwarp();
      }
    }
  }
  asm volatile("barrier.cluster.arrive.release.aligned;" ::: "memory");
  asm volatile("barrier.cluster.wait.acquire.aligned;" ::: "memory");
}
}

namespace g1 {
#define G1_NST 3
constexpr int NST = G1_NST;
constexpr uint32_t STAGE = 49152;
constexpr uint32_t OFF_STG = NST * STAGE;
constexpr uint32_t STG_BYTES = NST == 3 ? 65536 : 32768;
constexpr uint32_t OFF_BAR = OFF_STG + STG_BYTES;
constexpr uint32_t SMEM_BYTES = OFF_BAR + 128 + 1024;
constexpr int NTILES = 16 * 32;

__device__ __forceinline__ void role(const CUtensorMap& tmX, const CUtensorMap& tmWk, const CUtensorMap& tmWv, const CUtensorMap& tmKVst,
                                     uint8_t* smem_raw, int cta, int ncta) {
  const uint32_t sb = (smem_u32(smem_raw) + 1023) & ~1023u;
  const int tid = threadIdx.x, lane = tid & 31;
  const int warp = __shfl_sync(0xffffffffu, tid >> 5, 0);
  const int wg = warp >> 2, w4 = warp & 3;
  const uint32_t full = sb + OFF_BAR, empty = full + NST * 8;
  if (tid == 0) {
    for (int i = 0; i < NST; i++) { mbar_init(full + i * 8, 1); mbar_init(empty + i * 8, 2); }
    asm volatile("fence.mbarrier_init.release.cluster;" ::: "memory");
    fence_async_smem();
  }
  __syncthreads();
  const int ntile = cta < NTILES ? (NTILES - cta + ncta - 1) / ncta : 0;
  const int total = ntile * 10;
  const bool t0 = tid == 0, lead = (tid & 127) == 0;
  auto issue = [&](int it) {
    const int t = cta + (it / 10) * ncta, kb = it % 10, m = t >> 5, n = t & 31, st = it % NST;
    const uint32_t a = sb + st * STAGE, fb = full + st * 8;
    expect_if(t0, fb, STAGE);
    tma2d_if(t0, a, &tmX, kb * 64, m * 128, fb);
    const CUtensorMap* tw = n < 16 ? &tmWk : &tmWv;
#pragma unroll
    for (int i = 0; i < 4; i++) tma2d_if(t0, a + 16384 + i * 8192, tw, (n & 15) * 256 + i * 64, kb * 64, fb);
  };
  for (int it = 0; it < NST && it < total; it++) issue(it);
  if (tid == 0 && ntile > 0 && (cta & 31) < 7) tma2d_prefetch(&tmX, (NST + (cta & 31)) * 64, (cta >> 5) * 128);
  __syncwarp();

  float acc[128];
  int it = 0, pending_m = -1;
  for (int ti = 0; ti < ntile; ti++) {
    const int t = cta + ti * ncta, m = t >> 5, n = t & 31;
#pragma unroll 1
    for (int kb = 0; kb < 10; kb++, it++) {
      const int st = it % NST;
      bwait(full + st * 8, (it / NST) & 1);
      const uint32_t a = sb + st * STAGE;
      const uint64_t da = desc_k(a + wg * 8192), db = desc_mn(a + 16384);
      wg_fence();
#pragma unroll
      for (int k = 0; k < 4; k++) wgmma_n256(acc, da + k * 2, db + k * 128, (kb | k) != 0);
      wg_commit();
      if (kb > 0) {
        wg_wait<1>();
        const int pst = (it - 1) % NST;
        arrive_if(lead, empty + pst * 8);
        if (it - 1 + NST < total) { bwait(empty + pst * 8, ((it - 1) / NST) & 1); issue(it - 1 + NST); }
      }
      if (kb == 3 && pending_m >= 0) publish_if(lead, &g_flags.kv[pending_m]);
    }
    wg_wait<0>();

    {
      const int pst = (it - 1) % NST;
      arrive_if(lead, empty + pst * 8);
      if (it - 1 + NST < total) { bwait(empty + pst * 8, ((it - 1) / NST) & 1); issue(it - 1 + NST); }
    }
    constexpr int NR = NST == 3 ? 1 : 2;
    constexpr int NB = 4 / NR;
    const uint32_t stg = sb + OFF_STG + wg * (STG_BYTES / 2);
    const int q4 = lane >> 3, rr = lane & 7;
    const int row = w4 * 16 + (q4 & 1) * 8 + rr;
#pragma unroll
    for (int r = 0; r < NR; r++) {
      if ((tid & 127) == 0) bulk_wait_read0();
      bar_sync(1 + wg, 128);
#pragma unroll
      for (int jj = 0; jj < 8 * NB; jj += 2) {
        const int j = r * 8 * NB + jj;
        const int ch = (jj + (q4 >> 1)) & 7;
        stsm4(stg + (jj >> 3) * 8192 + row * 128 + ((ch ^ rr) << 4),
              pack_bf16(acc[4 * j], acc[4 * j + 1]), pack_bf16(acc[4 * j + 2], acc[4 * j + 3]),
              pack_bf16(acc[4 * j + 4], acc[4 * j + 5]), pack_bf16(acc[4 * j + 6], acc[4 * j + 7]));
      }
      fence_async_smem();
      bar_sync(1 + wg, 128);
      if (ti <= 1) {
        const int t7 = tid & 127;
#pragma unroll 4
        for (int q = 0; q < 4 * NB; q++) {
          const int p = q * 128 + t7, rw = p / (8 * NB), c = p % (8 * NB);
          const uint4 v = lds128u(stg + (c >> 3) * 8192 + rw * 128 + (((c & 7) ^ (rw & 7)) << 4));
          __stcg(reinterpret_cast<uint4*>(g_KV + (size_t)(m * 128 + wg * 64 + rw) * 8192 + n * 256 + r * NB * 64 + c * 8), v);
        }
      } else if ((tid & 127) == 0) {
#pragma unroll
        for (int i = 0; i < NB; i++) tma2d_store(&tmKVst, stg + i * 8192, n * 256 + (r * NB + i) * 64, m * 128 + wg * 64);
        bulk_commit();
      }
    }
    pending_m = m;
    if (ti <= 1) {

      __threadfence();
      bar_sync(1 + wg, 128);
      if (lead) asm volatile("red.relaxed.gpu.global.add.u32 [%0],1;" ::"l"(&g_flags.kv[m]) : "memory");
      __syncwarp();
      pending_m = -1;

    }
  }
  if (pending_m >= 0) publish_if(lead, &g_flags.kv[pending_m]);
}
}

struct K1Maps { CUtensorMap wq80, wk80, wv80, wo, wo4, kv32, kvm, x, wk64, wv64, kvst; };
constexpr uint32_t K1_SMEM = chain::SMEM_BYTES > g1::SMEM_BYTES ? chain::SMEM_BYTES : g1::SMEM_BYTES;

__global__ void __cluster_dims__(8, 1, 1) __launch_bounds__(256, 1)
k1_kernel(const __grid_constant__ K1Maps mp, const bf16* __restrict__ mem0, const bf16* __restrict__ x
          ) {
  extern __shared__ uint8_t smem_raw[];
  if (threadIdx.x == 32) s_par = (int)(*reinterpret_cast<volatile unsigned*>(&g_epoch) & 1);
  if (blockIdx.x == gridDim.x - 1) {
    if (threadIdx.x >= 224) {
      const int par = (int)(*reinterpret_cast<volatile unsigned*>(&g_epoch) & 1);
      for (int i = threadIdx.x - 224; i < (int)(sizeof(Flags) / 4); i += 32) reinterpret_cast<unsigned*>(&g_flags2[par ^ 1])[i] = 0;
      if (threadIdx.x == 224) g_cur = (unsigned)par;
      __threadfence();
      __syncwarp();
      asm volatile("griddepcontrol.launch_dependents;");
    }
  } else {
    asm volatile("griddepcontrol.launch_dependents;");
  }
  if (blockIdx.x < 64) chain::chain_role(mp.wq80, mp.wk80, mp.wv80, mp.wo, mp.wo4, mp.kv32, mp.kvm, mem0, x, smem_raw);
  else g1::role(mp.x, mp.wk64, mp.wv64, mp.kvst, smem_raw, blockIdx.x - 64, gridDim.x - 64);
  if (blockIdx.x == 0 && threadIdx.x == 0
     ) g_epoch = g_epoch + 1;
}

#define PUBLISH(p) do { fence_async_all(); red_release((p), 1u); } while (0)
namespace k2 {
constexpr int NST = 3;
constexpr uint32_t STAGE = 32768;
constexpr uint32_t OFF_BAR = 110592;
constexpr uint32_t SMEM_BYTES = OFF_BAR + 128 + 1024;
constexpr int B_FULL = 0, B_EMPTY = 3, B_KV = 6, B_KM = 7;
constexpr int NG4 = 160;
#define POST_AFTER 4
constexpr int NPOST = 80;
#define SPLIT_FROM_ 10
constexpr int SPLIT_FROM = SPLIT_FROM_;
constexpr int MAXSPLIT = 16;
#define NSPL_A 4
#define NSPL_B 8
#define SPLIT_B_FROM 14
#define NSPL_C 16
constexpr __host__ __device__ int nsplit_of(int m) { return m == 15 ? NSPL_C : (m >= SPLIT_B_FROM ? NSPL_B : (m >= SPLIT_FROM ? NSPL_A : 1)); }
#define HALF_FROM 15
constexpr __host__ __device__ int g3_items(int m) { return m >= HALF_FROM ? 160 : 5 * nsplit_of(m); }
constexpr __host__ __device__ int group_items(int r) { return (r < 16 ? 32 : 0) + (r > 0 ? g3_items(r - 1) : 0) + (r == POST_AFTER ? NPOST : 0); }
constexpr __host__ __device__ int total_items() { int t = NG4; for (int r = 0; r <= 16; r++) t += group_items(r); return t; }
struct Maps { CUtensorMap x, wq, kv128, kvm, o64, o, wo, out; };

__device__ __forceinline__ void gemm128(float (&acc)[64], const CUtensorMap* ta, int a_c0, int a_row, const CUtensorMap* tb, int b_col, int b_row0,
                                        int nkb, uint32_t sb, int tid, int wg, const unsigned* flag = nullptr, unsigned target = 0) {
  const uint32_t full = sb + OFF_BAR + B_FULL * 8, empty = sb + OFF_BAR + B_EMPTY * 8;
  const bool t0 = tid == 0, lead = (tid & 127) == 0;
  auto issue_b = [&](int it) {
    const int st = it % NST;
    const uint32_t a = sb + st * STAGE, fb = full + st * 8;
    expect_if(t0, fb, STAGE);
    tma2d_if(t0, a + 16384, tb, b_col, b_row0 + it * 64, fb);
    tma2d_if(t0, a + 24576, tb, b_col + 64, b_row0 + it * 64, fb);
  };
  auto issue_a = [&](int it) {
    const int st = it % NST;
    tma2d_if(t0, sb + st * STAGE, ta, a_c0 + it * 64, a_row, full + st * 8);
  };
  auto issue = [&](int it) { issue_b(it); issue_a(it); };
  for (int it = 0; it < NST && it < nkb; it++) issue_b(it);
  if (flag != nullptr) {
    if (t0) { wait_flag(flag, target); fence_async_all(); }
    __syncthreads();
  }
  for (int it = 0; it < NST && it < nkb; it++) issue_a(it);
#pragma unroll 1
  for (int it = 0; it < nkb; it++) {
    const int st = it % NST;
    bwait(full + st * 8, (it / NST) & 1);
    const uint32_t a = sb + st * STAGE;
    const uint64_t da = desc_k(a + wg * 8192), db = desc_mn(a + 16384);
    wg_fence();
#pragma unroll
    for (int k = 0; k < 4; k++) wgmma_n128(acc, da + k * 2, db + k * 128, (it | k) != 0);
    wg_commit();
    if (it > 0) {
      wg_wait<1>();
      const int pst = (it - 1) % NST;
      arrive_if(lead, empty + pst * 8);
      if (it - 1 + NST < nkb) { bwait(empty + pst * 8, ((it - 1) / NST) & 1); issue(it - 1 + NST); }
    }
  }
  wg_wait<0>();
}

__device__ __forceinline__ void stage_tile(const float (&c)[64], uint32_t stg, int row0, int lane) {
  const int q4 = lane >> 3, rr = lane & 7;
  const int row = row0 + (q4 & 1) * 8 + rr;
#pragma unroll
  for (int j = 0; j < 16; j += 2) {
    const int ch = (j + (q4 >> 1)) & 7;
    stsm4(stg + (j >> 3) * 16384 + row * 128 + ((ch ^ rr) << 4),
          pack_bf16(c[4 * j], c[4 * j + 1]), pack_bf16(c[4 * j + 2], c[4 * j + 3]),
          pack_bf16(c[4 * j + 4], c[4 * j + 5]), pack_bf16(c[4 * j + 6], c[4 * j + 7]));
  }
}

__device__ __forceinline__ void g2_item(const Maps& mp, int m, int h, uint32_t sb, int tid) {
  const int lane = tid & 31, warp = __shfl_sync(0xffffffffu, tid >> 5, 0), wg = warp >> 2, w4 = warp & 3;
  float acc[64];
  gemm128(acc, &mp.x, 0, m * 128, &mp.wq, h * 128, 0, 10, sb, tid, wg);
  uint32_t qa[8][4];
#pragma unroll
  for (int k = 0; k < 8; k++) {
    qa[k][0] = pack_bf16(acc[8 * k], acc[8 * k + 1]); qa[k][1] = pack_bf16(acc[8 * k + 2], acc[8 * k + 3]);
    qa[k][2] = pack_bf16(acc[8 * k + 4], acc[8 * k + 5]); qa[k][3] = pack_bf16(acc[8 * k + 6], acc[8 * k + 7]);
  }
  __syncthreads();
  const uint32_t bkv = sb + OFF_BAR + B_KV * 8, bkm = sb + OFF_BAR + B_KM * 8;
  const uint32_t sK = sb, sV = sb + STAGE, sM = sb + 2 * STAGE;
  if (tid == 0) {
    wait_flag(&g_flags.kv[m], 64);
    fence_async_all();
    mbar_expect(bkv, 65536);
    tma2d(sK, &mp.kv128, h * 128, m * 128, bkv);
    tma2d(sK + 16384, &mp.kv128, h * 128 + 64, m * 128, bkv);
    tma2d(sV, &mp.kv128, 4096 + h * 128, m * 128, bkv);
    tma2d(sV + 16384, &mp.kv128, 4096 + h * 128 + 64, m * 128, bkv);
  }
  __syncwarp();
  const int seg = 2 * wg + (w4 >> 1), hi = w4 & 1;
  const int q4 = lane >> 3, rr = lane & 7, g = lane >> 2, t = lane & 3;
  float sc[5][4];
#pragma unroll
  for (int n = 0; n < 5; n++) sc[n][0] = sc[n][1] = sc[n][2] = sc[n][3] = 0.f;
  mbar_wait(bkv, 0);
#pragma unroll
  for (int n = 0; n < 4; n++) {
    if (n < 2 || hi) {
      const uint32_t kr = sK + (seg * 32 + n * 8 + rr) * 128;
#pragma unroll
      for (int k2 = 0; k2 < 4; k2++) {
        uint32_t b[4];
        ldsm4(b, kr + (k2 >> 1) * 16384 + ((((k2 & 1) * 4 + q4) ^ rr) << 4));
        mma16816(sc[n + 1], qa[2 * k2], b[0], b[1]);
        mma16816(sc[n + 1], qa[2 * k2 + 1], b[2], b[3]);
      }
    }
  }
  __syncthreads();
  const bool lead = (tid & 127) == 0;
  const uint32_t bkmw = bkm + wg * 8;
  {
  if (lead) {
    wait_flag(&g_flags.mem[4 * m + 2 * wg], 64);
    wait_flag(&g_flags.mem[4 * m + 2 * wg + 1], 64);
    fence_async_all();
    mbar_expect(bkmw, 8192);
    for (int i = 2 * wg; i < 2 * wg + 2; i++) {
      tma2d(sM + i * 4096, &mp.kvm, 0, ((4 * m + i) * H_ + h) * 16, bkmw);
      tma2d(sM + i * 4096 + 2048, &mp.kvm, 64, ((4 * m + i) * H_ + h) * 16, bkmw);
    }
  }
  __syncwarp();
  mbar_wait(bkmw, 0);
  }

  {
    const uint32_t kr = sM + seg * 4096 + rr * 128;
#pragma unroll
    for (int k2 = 0; k2 < 4; k2++) {
      uint32_t b[4];
      ldsm4(b, kr + (k2 >> 1) * 2048 + ((((k2 & 1) * 4 + q4) ^ rr) << 4));
      mma16816(sc[0], qa[2 * k2], b[0], b[1]);
      mma16816(sc[0], qa[2 * k2 + 1], b[2], b[3]);
    }
  }
  const int r0 = hi * 16 + g, r1 = r0 + 8;
  const float NEG = -1e30f;
#pragma unroll
  for (int n = 0; n < 4; n++) {
    const int k0 = n * 8 + 2 * t;
    if (k0 > r0) sc[n + 1][0] = NEG;
    if (k0 + 1 > r0) sc[n + 1][1] = NEG;
    if (k0 > r1) sc[n + 1][2] = NEG;
    if (k0 + 1 > r1) sc[n + 1][3] = NEG;
  }
  float m0 = NEG, m1 = NEG;
#pragma unroll
  for (int n = 0; n < 5; n++) { m0 = fmaxf(m0, fmaxf(sc[n][0], sc[n][1])); m1 = fmaxf(m1, fmaxf(sc[n][2], sc[n][3])); }
  m0 = fmaxf(m0, __shfl_xor_sync(0xffffffffu, m0, 1)); m1 = fmaxf(m1, __shfl_xor_sync(0xffffffffu, m1, 1));
  m0 = fmaxf(m0, __shfl_xor_sync(0xffffffffu, m0, 2)); m1 = fmaxf(m1, __shfl_xor_sync(0xffffffffu, m1, 2));
  const float sl2 = 0.08838834764831845f * 1.4426950408889634f;
  const float o0 = -m0 * sl2, o1 = -m1 * sl2;
  float s0 = 0.f, s1 = 0.f;
  uint32_t p[5][2];
#pragma unroll
  for (int n = 0; n < 5; n++) {
    const float e0 = ex2(fmaf(sc[n][0], sl2, o0)), e1 = ex2(fmaf(sc[n][1], sl2, o0));
    const float e2 = ex2(fmaf(sc[n][2], sl2, o1)), e3 = ex2(fmaf(sc[n][3], sl2, o1));
    s0 += e0 + e1; s1 += e2 + e3;
    p[n][0] = pack_bf16(e0, e1); p[n][1] = pack_bf16(e2, e3);
  }
  s0 += __shfl_xor_sync(0xffffffffu, s0, 1); s1 += __shfl_xor_sync(0xffffffffu, s1, 1);
  s0 += __shfl_xor_sync(0xffffffffu, s0, 2); s1 += __shfl_xor_sync(0xffffffffu, s1, 2);
  const float i0 = 1.0f / s0, i1 = 1.0f / s1;
  const uint32_t vrow = q4 == 0 ? sM + seg * 4096 + (8 + rr) * 128 : sV + (seg * 32 + (q4 - 1) * 8 + rr) * 128;
  const uint32_t vhalf = q4 == 0 ? 2048 : 16384;
  const uint32_t vlast = sV + (seg * 32 + 24 + rr) * 128;
  const uint32_t a0[4] = {p[0][0], p[0][1], p[1][0], p[1][1]}, a1[4] = {p[2][0], p[2][1], p[3][0], p[3][1]};
#pragma unroll
  for (int c4 = 0; c4 < 4; c4++) {
    uint32_t bl[4];
    if (hi) ldsm4t(bl, vlast + (c4 >> 1) * 16384 + ((((c4 & 1) * 4 + q4) ^ rr) << 4));
#pragma unroll
    for (int i = 0; i < 4; i++) {
      const int c = c4 * 4 + i;
      uint32_t b[4];
      ldsm4t(b, vrow + (c >> 3) * vhalf + (((c & 7) ^ rr) << 4));
      float o[4] = {0.f, 0.f, 0.f, 0.f};
      mma16816(o, a0, b[0], b[1]);
      mma16816(o, a1, b[2], b[3]);
      if (hi) {
        asm volatile("mma.sync.aligned.m16n8k8.row.col.f32.bf16.bf16.f32 {%0,%1,%2,%3},{%4,%5},{%6},{%0,%1,%2,%3};"
                     : "+f"(o[0]), "+f"(o[1]), "+f"(o[2]), "+f"(o[3]) : "r"(p[4][0]), "r"(p[4][1]), "r"(bl[i]));
      }
      acc[4 * c] = o[0] * i0; acc[4 * c + 1] = o[1] * i0; acc[4 * c + 2] = o[2] * i1; acc[4 * c + 3] = o[3] * i1;
    }
  }

  stage_tile(acc, sK, wg * 64 + w4 * 16, lane);
  fence_async_smem();
  bar_sync(1 + wg, 128);
  if (m >= HALF_FROM) {
    const int t = tid & 127;
#pragma unroll
    for (int it = 0; it < 8; it++) {
      const int p = it * 128 + t, row = p >> 4, c16 = p & 15;
      const uint4 v = lds128u(sK + (c16 >> 3) * 16384 + (wg * 64 + row) * 128 + (((c16 & 7) ^ (row & 7)) << 4));
      __stcg(reinterpret_cast<uint4*>(g_O + (size_t)(m * 128 + wg * 64 + row) * HD_ + h * 128 + c16 * 8), v);
    }
    __threadfence();
    bar_sync(1 + wg, 128);

    if (lead) asm volatile("red.relaxed.gpu.global.add.u32 [%0],1;" ::"l"(&g_flags.oh[(m - 14) * 2 + wg]) : "memory");

  } else if (lead) {
    tma2d_store(&mp.o64, sK + wg * 8192, h * 128, m * 128 + wg * 64);
    tma2d_store(&mp.o64, sK + 16384 + wg * 8192, h * 128 + 64, m * 128 + wg * 64);
    bulk_commit();
    bulk_wait0();
    PUBLISH(&g_flags.o[m]);
  }
}

__device__ __forceinline__ void g3h_item(const Maps& mp, int m, int hf, int n, int ks, bf16* __restrict__ out, uint32_t sb, int tid) {
  const int lane = tid & 31, warp = __shfl_sync(0xffffffffu, tid >> 5, 0), wg = warp >> 2;
  const uint32_t fb = sb + OFF_BAR + B_FULL * 8, fa = fb + 8;
  if (tid == 0) {
    mbar_expect(fb, 65536);
    for (int kb = 0; kb < 4; kb++) {
      tma2d(sb + kb * 16384, &mp.wo, n * 128, ks * 256 + kb * 64, fb);
      tma2d(sb + kb * 16384 + 8192, &mp.wo, n * 128 + 64, ks * 256 + kb * 64, fb);
    }
    wait_flag(&g_flags.oh[(m - 14) * 2 + hf], 32);
    fence_async_all();
    mbar_expect(fa, 32768);
    for (int kb = 0; kb < 4; kb++) tma2d(sb + 65536 + kb * 8192, &mp.o64, ks * 256 + kb * 64, m * 128 + hf * 64, fa);
  }
  __syncwarp();
  bwait(fb, 0);
  bwait(fa, 0);
  float acc[32];
  wg_fence();
#pragma unroll
  for (int kb = 0; kb < 4; kb++) {
    const uint64_t da = desc_k(sb + 65536 + kb * 8192), db = desc_mn(sb + kb * 16384 + wg * 8192);
#pragma unroll
    for (int k = 0; k < 4; k++) wgmma_n64(acc, da + k * 2, db + k * 128, (kb | k) != 0);
  }
  wg_commit();
  wg_wait<0>();

  float4* part = reinterpret_cast<float4*>(g_part + (size_t)(((m - 10) * 5 + n) * MAXSPLIT) * 16384 + (size_t)hf * 16 * 8192);
#pragma unroll
  for (int i = 0; i < 8; i++) __stcg(part + (size_t)ks * 2048 + i * 256 + tid, make_float4(acc[4 * i], acc[4 * i + 1], acc[4 * i + 2], acc[4 * i + 3]));
  __threadfence();
  __syncthreads();
  if (tid == 0) {
    unsigned* cnt = &g_flags.part[m == 15 ? 25 + hf * 5 + n : (hf == 0 ? 20 + n : 35 + n)];

    asm volatile("red.relaxed.gpu.global.add.u32 [%0],1;" ::"l"(cnt) : "memory");
    wait_flag(cnt, 16u);

  }
  __syncthreads();
  if (tid < 128) {
    const int i = ks >> 1, w = ks & 1;
    float4 v[16];
#pragma unroll
    for (int k = 0; k < 16; k++) v[k] = __ldcg(part + (size_t)k * 2048 + i * 256 + w * 128 + tid);
    float4 s0 = make_float4(0.f, 0.f, 0.f, 0.f);
#pragma unroll
    for (int k = 0; k < 16; k++) { s0.x += v[k].x; s0.y += v[k].y; s0.z += v[k].z; s0.w += v[k].w; }
    const int row = m * 128 + hf * 64 + (tid >> 5) * 16 + (lane >> 2);
    bf16* o = out + (size_t)row * 1280 + n * 128 + w * 64 + i * 8 + (lane & 3) * 2;
    *reinterpret_cast<uint32_t*>(o) = pack_bf16(s0.x, s0.y);
    *reinterpret_cast<uint32_t*>(o + 8 * 1280) = pack_bf16(s0.z, s0.w);
  }

}

__device__ __forceinline__ void g3_item(const Maps& mp, int m, int n, int ks, int nsplit, bf16* __restrict__ out, uint32_t sb, int tid, volatile int* s_flag) {
  const int lane = tid & 31, warp = __shfl_sync(0xffffffffu, tid >> 5, 0), wg = warp >> 2, w4 = warp & 3;
  float acc[64];
  const int nkb = 64 / nsplit;
  gemm128(acc, &mp.o, ks * nkb * 64, m * 128, &mp.wo, n * 128, ks * nkb * 64, nkb, sb, tid, wg, &g_flags.o[m], 64);

  if (nsplit > 1) {
    float4* part = reinterpret_cast<float4*>(g_part + (size_t)(((m - 10) * 5 + n) * MAXSPLIT) * 16384);
    __syncthreads();
#pragma unroll
    for (int i = 0; i < 16; i++) sts128f(sb + (i * 256 + tid) * 16, acc[4 * i], acc[4 * i + 1], acc[4 * i + 2], acc[4 * i + 3]);
    fence_async_smem();
    __syncthreads();
    if (tid == 0) {
      unsigned* cnt = &g_flags.part[(m - 10) * 5 + n];
#pragma unroll
      for (int i = 0; i < 4; i++)
        asm volatile("cp.async.bulk.global.shared::cta.bulk_group [%0],[%1],16384;" ::"l"(part + (size_t)ks * 4096 + i * 1024), "r"(sb + i * 16384) : "memory");
      bulk_commit();
      bulk_wait0();
      PUBLISH(cnt);
      wait_flag(cnt, (unsigned)nsplit);

    }
    __syncthreads();
    const int per = 16 / nsplit;
    const int row = m * 128 + wg * 64 + w4 * 16 + (lane >> 2);
    for (int i = ks * per; i < (ks + 1) * per; i++) {
      float4 v[MAXSPLIT];
#pragma unroll
      for (int k = 0; k < MAXSPLIT; k++)
        if (k < nsplit) v[k] = __ldcg(part + (size_t)k * 4096 + i * 256 + tid);
      float4 s0 = make_float4(0.f, 0.f, 0.f, 0.f);
#pragma unroll
      for (int k = 0; k < MAXSPLIT; k++)
        if (k < nsplit) { s0.x += v[k].x; s0.y += v[k].y; s0.z += v[k].z; s0.w += v[k].w; }
      bf16* o = out + (size_t)row * 1280 + n * 128 + i * 8 + (lane & 3) * 2;
      *reinterpret_cast<uint32_t*>(o) = pack_bf16(s0.x, s0.y);
      *reinterpret_cast<uint32_t*>(o + 8 * 1280) = pack_bf16(s0.z, s0.w);
    }

    return;
  }
  __syncthreads();
  stage_tile(acc, sb, wg * 64 + w4 * 16, lane);
  fence_async_smem();
  __syncthreads();
  if (tid == 0) {
    tma2d_store(&mp.out, sb, n * 128, m * 128);
    tma2d_store(&mp.out, sb + 16384, n * 128 + 64, m * 128);
    bulk_commit();
    bulk_wait0();
  }
}
}

namespace conv {
constexpr uint32_t U_CH = 5120;
constexpr uint32_t OFF_R = 8 * U_CH;
constexpr uint32_t R1_OFF = 4288, R_CH = R1_OFF + 4224;
static_assert(OFF_R + 8 * R_CH <= k2::OFF_BAR, "conv smem");

__device__ __forceinline__ uint32_t lds32(uint32_t a) { uint32_t v; asm volatile("ld.shared.u32 %0,[%1];" : "=r"(v) : "r"(a) : "memory"); return v; }
__device__ __forceinline__ void sts128u(uint32_t a, uint32_t x, uint32_t y, uint32_t z, uint32_t w) {
  asm volatile("st.shared.v4.u32 [%0],{%1,%2,%3,%4};" ::"r"(a), "r"(x), "r"(y), "r"(z), "r"(w) : "memory");
}
__device__ __forceinline__ __nv_bfloat162 as_bf2(uint32_t v) { return *reinterpret_cast<__nv_bfloat162*>(&v); }
__device__ __forceinline__ uint32_t as_u32(__nv_bfloat162 v) { return *reinterpret_cast<uint32_t*>(&v); }

template <int M0, int NSTEP4>
__device__ __forceinline__ void phase(float (&acc)[2][8][4], uint32_t (&P)[8][2], int x_first, uint32_t vadr, uint32_t ub, int q4, int rr) {
#pragma unroll 1
  for (int it = 0; it < NSTEP4; it++) {
    const int xb = x_first + 4 * it;
    const int shb = (xb + 3) >> 2;
#pragma unroll
    for (int u = 0; u < 4; u++) {
      const int x = xb + u;
      const int r = (1 + u) & 3;
      const int sh = u == 0 ? shb : (x + 3) >> 2;
      const int ch0 = r == 0 ? 0 : (8 - 2 * r);
      uint32_t a[2][4];
#pragma unroll
      for (int m = M0; m < 2; m++) {
        int ri = 16 * m + (q4 & 1) * 8 + rr + 8 - sh;
        if (m == M0) ri = ri < 0 ? (ri & 7) : ri;
        ldsm4(a[m], ub + ri * 128 + (((ch0 + (q4 >> 1)) ^ (ri & 7)) << 4));
      }
#pragma unroll
      for (int al = 0; al < 8; al++) {
        const int slot = (2 * u + al) & 7;
#pragma unroll
        for (int m = M0; m < 2; m++) mma16816(acc[m][al], a[m], P[slot][0], P[slot][1]);
        if (al < 2) {
          P[slot][0] = lds32(vadr - 16 * (2 * x + 8 + al));
          P[slot][1] = lds32(vadr - 16 * (2 * x + 7 + al));
        }
      }
    }
  }
}

__device__ __forceinline__ void pre_item(int tt, int cg, const bf16* __restrict__ k, const bf16* __restrict__ v, const bf16* __restrict__ shift_k, int tid) {
  const int d0 = cg * 64 + (tid & 7) * 8, t0 = tt * 256 + (tid >> 3) * 8;
  uint4 kr[11], vr[8];
#pragma unroll
  for (int j = 0; j < 11; j++) kr[j] = (j >= 3 || t0 > 0) ? __ldg(reinterpret_cast<const uint4*>(k + (size_t)(t0 - 3 + j) * D_ + d0)) : make_uint4(0, 0, 0, 0);
#pragma unroll
  for (int j = 0; j < 8; j++) vr[j] = __ldg(reinterpret_cast<const uint4*>(v + (size_t)(t0 + j) * D_ + d0));
  uint32_t sw[4][4];
#pragma unroll
  for (int c = 0; c < 4; c++) {
    const uint2 w0 = __ldg(reinterpret_cast<const uint2*>(shift_k + (d0 + 2 * c) * 4)), w1 = __ldg(reinterpret_cast<const uint2*>(shift_k + (d0 + 2 * c + 1) * 4));
    sw[0][c] = __byte_perm(w0.x, w1.x, 0x5410); sw[1][c] = __byte_perm(w0.x, w1.x, 0x7632);
    sw[2][c] = __byte_perm(w0.y, w1.y, 0x5410); sw[3][c] = __byte_perm(w0.y, w1.y, 0x7632);
  }
  uint32_t kvw[8][4];
#pragma unroll
  for (int j = 0; j < 8; j++) {
    const uint32_t x0[4] = {kr[j].x, kr[j].y, kr[j].z, kr[j].w}, x1[4] = {kr[j + 1].x, kr[j + 1].y, kr[j + 1].z, kr[j + 1].w};
    const uint32_t x2[4] = {kr[j + 2].x, kr[j + 2].y, kr[j + 2].z, kr[j + 2].w}, x3[4] = {kr[j + 3].x, kr[j + 3].y, kr[j + 3].z, kr[j + 3].w};
    const uint32_t vv[4] = {vr[j].x, vr[j].y, vr[j].z, vr[j].w};
#pragma unroll
    for (int c = 0; c < 4; c++) {
      __nv_bfloat162 a = __hmul2_rn(as_bf2(x0[c]), as_bf2(sw[3][c]));
      a = __hadd2_rn(a, __hmul2_rn(as_bf2(x1[c]), as_bf2(sw[2][c])));
      a = __hadd2_rn(a, __hmul2_rn(as_bf2(x2[c]), as_bf2(sw[1][c])));
      a = __hadd2_rn(a, __hmul2_rn(as_bf2(x3[c]), as_bf2(sw[0][c])));
      kvw[j][c] = as_u32(__hmul2_rn(a, as_bf2(vv[c])));
    }
  }
#pragma unroll
  for (int c = 0; c < 4; c++) {
    uint4 e, o;
    e.x = __byte_perm(kvw[0][c], kvw[1][c], 0x5410); e.y = __byte_perm(kvw[2][c], kvw[3][c], 0x5410);
    e.z = __byte_perm(kvw[4][c], kvw[5][c], 0x5410); e.w = __byte_perm(kvw[6][c], kvw[7][c], 0x5410);
    o.x = __byte_perm(kvw[0][c], kvw[1][c], 0x7632); o.y = __byte_perm(kvw[2][c], kvw[3][c], 0x7632);
    o.z = __byte_perm(kvw[4][c], kvw[5][c], 0x7632); o.w = __byte_perm(kvw[6][c], kvw[7][c], 0x7632);
    __stcg(reinterpret_cast<uint4*>(g_uT + (size_t)(d0 + 2 * c) * S_ + t0), e);
    __stcg(reinterpret_cast<uint4*>(g_uT + (size_t)(d0 + 2 * c + 1) * S_ + t0), o);
  }
  __threadfence();
  __syncthreads();
  if (tid == 0) atomicAdd(&g_flags.cva[cg], 1u);
}

__device__ __forceinline__ void post_item(int tt, int cg, const bf16* __restrict__ q, bf16* __restrict__ out, int tid) {
  const int d0 = cg * 64 + (tid & 7) * 8, t0 = tt * 256 + (tid >> 3) * 8;
  uint4 qr[8];
#pragma unroll
  for (int j = 0; j < 8; j++) qr[j] = __ldg(reinterpret_cast<const uint4*>(q + (size_t)(t0 + j) * D_ + d0));
  if (tid == 0) wait_flag(&g_flags.cvb[cg], 8);
  __syncthreads();
  uint32_t zw[8][4];
#pragma unroll
  for (int c = 0; c < 4; c++) {
    const uint4 e = __ldcg(reinterpret_cast<const uint4*>(g_uT + (size_t)(d0 + 2 * c) * S_ + t0));
    const uint4 o = __ldcg(reinterpret_cast<const uint4*>(g_uT + (size_t)(d0 + 2 * c + 1) * S_ + t0));
    zw[0][c] = __byte_perm(e.x, o.x, 0x5410); zw[1][c] = __byte_perm(e.x, o.x, 0x7632);
    zw[2][c] = __byte_perm(e.y, o.y, 0x5410); zw[3][c] = __byte_perm(e.y, o.y, 0x7632);
    zw[4][c] = __byte_perm(e.z, o.z, 0x5410); zw[5][c] = __byte_perm(e.z, o.z, 0x7632);
    zw[6][c] = __byte_perm(e.w, o.w, 0x5410); zw[7][c] = __byte_perm(e.w, o.w, 0x7632);
  }
#pragma unroll
  for (int j = 0; j < 8; j++) {
    const uint4 qv = qr[j];
    uint4 o;
    o.x = as_u32(__hmul2_rn(as_bf2(qv.x), as_bf2(zw[j][0]))); o.y = as_u32(__hmul2_rn(as_bf2(qv.y), as_bf2(zw[j][1])));
    o.z = as_u32(__hmul2_rn(as_bf2(qv.z), as_bf2(zw[j][2]))); o.w = as_u32(__hmul2_rn(as_bf2(qv.w), as_bf2(zw[j][3])));
    *reinterpret_cast<uint4*>(out + (size_t)(t0 + j) * 1280 + 640 + d0) = o;
  }
}

__device__ __forceinline__ void item(int d0, const bf16* __restrict__ ssm_k, const bf16* __restrict__ ssm_D, uint32_t sb, int tid) {
  const int lane = tid & 31, warp = tid >> 5;
  const uint32_t r0 = sb + OFF_R + warp * R_CH, r1 = r0 + R1_OFF;
  const uint32_t ub = sb + warp * U_CH;
  {
    const uint4* src = reinterpret_cast<const uint4*>(ssm_k + (size_t)(d0 + warp) * S_);
    uint4 e[8];
#pragma unroll
    for (int j = 0; j < 8; j++) e[j] = __ldg(src + lane + 32 * j);
    if (lane < 8) sts128u(r1 + (1024 + 4 * lane) * 4, 0, 0, 0, 0);
    sts128u(ub + lane * 32, 0, 0, 0, 0);
    sts128u(ub + lane * 32 + 16, 0, 0, 0, 0);
#pragma unroll
    for (int j = 0; j < 8; j++) {
      const int c = lane + 32 * j;
      sts128u(r1 + (1020 - 4 * c) * 4, __byte_perm(e[j].w, 0, 0x1032), __byte_perm(e[j].z, 0, 0x1032), __byte_perm(e[j].y, 0, 0x1032), __byte_perm(e[j].x, 0, 0x1032));
    }
  }
  __syncwarp();
#pragma unroll
  for (int it = 0; it < 9; it++) {
    const int i4 = lane + 32 * it;
    if (i4 < 264) {
      const uint4 w = lds128u(r1 + i4 * 16);
      const uint32_t prev = i4 > 0 ? lds32(r1 + i4 * 16 - 4) : 0u;
      sts128u(r0 + i4 * 16, __byte_perm(prev, w.x, 0x5432), __byte_perm(w.x, w.y, 0x5432), __byte_perm(w.y, w.z, 0x5432), __byte_perm(w.z, w.w, 0x5432));
    }
  }
  if (tid == 0) wait_flag(&g_flags.cva[d0 >> 6], 8);
  __syncthreads();
  {
    const uint4* src = reinterpret_cast<const uint4*>(g_uT + (size_t)(d0 + warp) * S_);
    uint4 e[8];
#pragma unroll
    for (int j = 0; j < 8; j++) e[j] = __ldcg(src + lane + 32 * j);
#pragma unroll
    for (int j = 0; j < 8; j++) {
      const int c = lane + 32 * j, ri = (c >> 3) + 8;
      sts128u(ub + ri * 128 + (((c & 7) ^ (ri & 7)) << 4), e[j].x, e[j].y, e[j].z, e[j].w);
    }
  }
  __syncwarp();

  const int g = lane >> 2, t = lane & 3, q4 = lane >> 3, rr = lane & 7;
  float acc[2][8][4];
#pragma unroll
  for (int a = 0; a < 2; a++)
#pragma unroll
    for (int b = 0; b < 8; b++) acc[a][b][0] = acc[a][b][1] = acc[a][b][2] = acc[a][b][3] = 0.f;
  const uint32_t vadr = ((g & 1) ? r1 : r0) + ((2048 - g + 2 * t) >> 1) * 4;
  uint32_t P[8][2];
#pragma unroll
  for (int al = 0; al < 8; al++) {
    P[al][0] = lds32(vadr - 16 * (-6 + al));
    P[al][1] = lds32(vadr - 16 * (-7 + al));
  }
  phase<0, 16>(acc, P, -3, vadr, ub, q4, rr);
  phase<1, 16>(acc, P, 61, vadr, ub, q4, rr);
  __syncwarp();

  {
    const bf16 Dv = ssm_D[d0 + warp];
    const __nv_bfloat162 D2 = __halves2bfloat162(Dv, Dv);
#pragma unroll
    for (int m = 0; m < 2; m++)
#pragma unroll
      for (int al = 0; al < 8; al++)
#pragma unroll
        for (int h = 0; h < 2; h++) {
          const int ri = 16 * m + 8 * h + g + 8;
          const uint32_t ad = ub + ri * 128 + ((al ^ (ri & 7)) << 4) + t * 4;
          const __nv_bfloat162 kv2 = as_bf2(lds32(ad));
          const __nv_bfloat162 y2 = as_bf2(pack_bf16(acc[m][al][2 * h], acc[m][al][2 * h + 1]));
          const uint32_t z = as_u32(__hadd2_rn(y2, __hmul2_rn(kv2, D2)));
          asm volatile("st.shared.u32 [%0],%1;" ::"r"(ad), "r"(z) : "memory");
        }
  }
  __syncwarp();
  {
    uint4* dst = reinterpret_cast<uint4*>(g_uT + (size_t)(d0 + warp) * S_);
#pragma unroll
    for (int j = 0; j < 8; j++) {
      const int c = lane + 32 * j, ri = (c >> 3) + 8;
      __stcg(dst + c, lds128u(ub + ri * 128 + (((c & 7) ^ (ri & 7)) << 4)));
    }
  }
  __threadfence();
  __syncthreads();
  if (tid == 0) atomicAdd(&g_flags.cvb[d0 >> 6], 1u);
}
}

struct ConvArgs { const bf16 *q, *k, *v, *shift_k, *ssm_k, *ssm_D; bf16* out; };

__global__ void __launch_bounds__(256, 2) k2_kernel(const __grid_constant__ k2::Maps mp, const ConvArgs ca) {
  extern __shared__ uint8_t smem_raw[];
  __shared__ int s_item;
  const uint32_t sb = (smem_u32(smem_raw) + 1023) & ~1023u;
  const int tid = threadIdx.x;
  if (tid == 0) {
    s_par = (int)*reinterpret_cast<volatile unsigned*>(&g_cur);
    s_item = (int)atomicAdd(&g_flags.ticket, 1u);
    const uint32_t bar = sb + k2::OFF_BAR;
    for (int i = 0; i < 3; i++) { mbar_init(bar + (k2::B_FULL + i) * 8, 1); mbar_init(bar + (k2::B_EMPTY + i) * 8, 2); }
    mbar_init(bar + k2::B_KV * 8, 1); mbar_init(bar + k2::B_KM * 8, 1); mbar_init(bar + k2::B_KM * 8 + 8, 1);
    asm volatile("fence.mbarrier_init.release.cluster;" ::: "memory");
    fence_async_smem();
  }
  __syncthreads();
  int item = s_item;
  __syncthreads();
  if (item < k2::NG4) {
    if (item < 80) conv::pre_item(item & 7, item >> 3, ca.k, ca.v, ca.shift_k, tid);
    else conv::item((item - 80) * 8, ca.ssm_k, ca.ssm_D, sb, tid);
  } else {
    item -= k2::NG4;
    int r = 0;
    while (item >= k2::group_items(r)) { item -= k2::group_items(r); r++; }
    const int n2 = r < 16 ? 32 : 0, n3 = r > 0 ? k2::g3_items(r - 1) : 0;
    if (item < n2) k2::g2_item(mp, r, item, sb, tid);
    else if (item < n2 + n3) {
      item -= n2;
      if (r - 1 >= HALF_FROM) k2::g3h_item(mp, r - 1, item / 80, (item % 80) >> 4, item & 15, ca.out, sb, tid);
      else {
        const int ns = k2::nsplit_of(r - 1);
        k2::g3_item(mp, r - 1, item / ns, item % ns, ns, ca.out, sb, tid, &s_item);
      }
    } else {
      item -= n2 + n3;
      conv::post_item(item & 7, item >> 3, ca.q, ca.out, tid);
    }
  }
}

typedef CUresult (*EncodeFn)(CUtensorMap*, CUtensorMapDataType, cuuint32_t, void*, const cuuint64_t*, const cuuint64_t*, const cuuint32_t*,
                             const cuuint32_t*, CUtensorMapInterleave, CUtensorMapSwizzle, CUtensorMapL2promotion, CUtensorMapFloatOOBfill);
static EncodeFn get_encode() {
  static EncodeFn fn = nullptr;
  if (!fn) {
    void* p = nullptr; cudaDriverEntryPointQueryResult st;
    cudaGetDriverEntryPoint("cuTensorMapEncodeTiled", &p, cudaEnableDefault, &st);
    fn = (EncodeFn)p;
  }
  return fn;
}
static CUtensorMap make_map2d(const void* base, uint64_t cols, uint64_t rows, uint64_t pitch_elems, uint32_t box_c, uint32_t box_r,
                              CUtensorMapSwizzle sw = CU_TENSOR_MAP_SWIZZLE_128B) {
  CUtensorMap m;
  cuuint64_t dims[2] = {cols, rows};
  cuuint64_t strides[1] = {pitch_elems * 2};
  cuuint32_t box[2] = {box_c, box_r};
  cuuint32_t es[2] = {1, 1};
  CUresult r = get_encode()(&m, CU_TENSOR_MAP_DATA_TYPE_BFLOAT16, 2, (void*)base, dims, strides, box, es, CU_TENSOR_MAP_INTERLEAVE_NONE, sw,
                            CU_TENSOR_MAP_L2_PROMOTION_L2_128B, CU_TENSOR_MAP_FLOAT_OOB_FILL_NONE);
  if (r != CUDA_SUCCESS) fprintf(stderr, "tensor map encode failed %d\n", (int)r);
  return m;
}

struct HostState {
  bool init;
  void* key[13];
  void* out;
  K1Maps k1;
  k2::Maps k2;
  int k1_clusters;
};
static HostState hs;

static void host_setup(void* const* d_in, void* d_out) {
  bool same = hs.init && hs.out == d_out;
  for (int i = 0; same && i < 13; i++) same = hs.key[i] == d_in[i];
  if (same) return;
  for (int i = 0; i < 13; i++) hs.key[i] = d_in[i];
  hs.out = d_out;
  void* kv; cudaGetSymbolAddress(&kv, g_KV);
  hs.k1.wq80 = make_map2d(d_in[2], 4096, 640, 4096, 64, 80);
  hs.k1.wk80 = make_map2d(d_in[3], 4096, 640, 4096, 64, 80);
  hs.k1.wv80 = make_map2d(d_in[4], 4096, 640, 4096, 64, 80);
  hs.k1.wo = make_map2d(d_in[5], 640, 4096, 640, 64, 64);
  hs.k1.wo4 = make_map2d(d_in[5], 640, 4096, 640, 16, 64, CU_TENSOR_MAP_SWIZZLE_32B);
  hs.k1.kv32 = make_map2d(kv, 8192, 2048, 8192, 64, 32);
  void* kvm; cudaGetSymbolAddress(&kvm, g_KVM);
  hs.k1.kvm = make_map2d(kvm, 128, 64 * 32 * 16, 128, 64, 16);
  hs.k1.x = make_map2d(d_in[0], 640, 2048, 640, 64, 128);
  hs.k1.wk64 = make_map2d(d_in[3], 4096, 640, 4096, 64, 64);
  hs.k1.wv64 = make_map2d(d_in[4], 4096, 640, 4096, 64, 64);
  hs.k1.kvst = make_map2d(kv, 8192, 2048, 8192, 64, 64);
  void* o; cudaGetSymbolAddress(&o, g_O);
  hs.k2.x = hs.k1.x;
  hs.k2.wq = make_map2d(d_in[2], 4096, 640, 4096, 64, 64);
  hs.k2.kv128 = make_map2d(kv, 8192, 2048, 8192, 64, 128);
  hs.k2.kvm = hs.k1.kvm;
  hs.k2.o64 = make_map2d(o, 4096, 2048, 4096, 64, 64);
  hs.k2.o = make_map2d(o, 4096, 2048, 4096, 64, 128);
  hs.k2.wo = hs.k1.wo;
  hs.k2.out = make_map2d(d_out, 1280, 2048, 1280, 64, 128);
  if (!hs.init) {
    cudaFuncSetAttribute(k2_kernel, cudaFuncAttributeMaxDynamicSharedMemorySize, k2::SMEM_BYTES);
    cudaFuncSetAttribute(k1_kernel, cudaFuncAttributeMaxDynamicSharedMemorySize, K1_SMEM);
    cudaLaunchConfig_t cfg = {};
    cfg.gridDim = dim3(128); cfg.blockDim = dim3(256); cfg.dynamicSmemBytes = K1_SMEM;
    cudaLaunchAttribute at[1];
    at[0].id = cudaLaunchAttributeClusterDimension; at[0].val.clusterDim.x = 8; at[0].val.clusterDim.y = 1; at[0].val.clusterDim.z = 1;
    cfg.attrs = at; cfg.numAttrs = 1;
    int n = 0;
    cudaOccupancyMaxActiveClusters(&n, k1_kernel, &cfg);
    if (n < 9) n = 9;
    if (n > 16) n = 16;
    hs.k1_clusters = n;
  }
  hs.init = true;
}
static void launch_k1(void* const* d_in, cudaStream_t st) {
  k1_kernel<<<hs.k1_clusters * 8, 256, K1_SMEM, st>>>(hs.k1, (const bf16*)d_in[1], (const bf16*)d_in[0]);
}

static void launch_k2(void* const* d_in, void* d_out, cudaStream_t st) {
  ConvArgs ca;
  ca.q = (const bf16*)d_in[7]; ca.k = (const bf16*)d_in[8]; ca.v = (const bf16*)d_in[9];
  ca.shift_k = (const bf16*)d_in[10]; ca.ssm_k = (const bf16*)d_in[11]; ca.ssm_D = (const bf16*)d_in[12]; ca.out = (bf16*)d_out;
  cudaLaunchConfig_t cfg = {};
  cfg.gridDim = dim3(k2::total_items()); cfg.blockDim = dim3(256); cfg.dynamicSmemBytes = k2::SMEM_BYTES; cfg.stream = st;
  cudaLaunchAttribute at[1];
  at[0].id = cudaLaunchAttributeProgrammaticStreamSerialization; at[0].val.programmaticStreamSerializationAllowed = 1;
  cfg.attrs = at; cfg.numAttrs = 1;
  cudaLaunchKernelEx(&cfg, k2_kernel, hs.k2, ca);
}

extern "C" void kernel_launch(void* const* d_in, const int* in_sizes, int n_in, void* d_out, int out_size) {
  cudaStream_t st = cudaStreamPerThread;
  host_setup(d_in, d_out);
  launch_k1(d_in, st);
  launch_k2(d_in, d_out, st);
}
```
